```python
import torch

def _softmax(x, axis=-1):
    return torch.softmax(x, dim=axis)
def _gelu(x):
    return torch.nn.functional.gelu(x, approximate="tanh")
def _silu(x):
    return torch.nn.functional.silu(x)
def _sigmoid(x):
    return torch.sigmoid(x)
def _layernorm(x, axis=-1, eps=1e-5):
    m = x.mean(dim=axis, keepdim=True)
    v = x.var(dim=axis, keepdim=True, unbiased=False)
    return (x - m) / torch.sqrt(v + eps)
def _scatter_add(tgt, idx, src, axis=0):
    return tgt.clone().index_add_(axis, idx, src)
def _segment_sum(src, seg, n):
    out = torch.zeros((n,) + src.shape[1:], dtype=src.dtype)
    return out.index_add_(0, seg, src)
def _pad(x, pw):
    flat = tuple(v for pair in reversed(pw) for v in pair)
    return torch.nn.functional.pad(x, flat)

kernel_name = 'standalone__mpnn_edge_mlp__graph'

def setup_inputs():

    _w = (lambda a: (lambda t: t.to(torch.bfloat16) if t.is_floating_point() else t)(torch.as_tensor(a)))
    N, deg, D, De = 10000, 16, 128, max(16, 1)
    E = N * deg
    return {
        "x": _w((lambda *s: torch.randn(*s, dtype=torch.bfloat16) * 0.05)(N, D)),
        "e_attr": _w((lambda *s: torch.randn(*s, dtype=torch.bfloat16) * 0.4)(E, De)),
        "src": _w((lambda lo, hi, *s: torch.randint(lo, hi, s))(0, N, E).to(torch.int64)),
        "dst": _w((lambda lo, hi, *s: torch.randint(lo, hi, s))(0, N, E).to(torch.int64)),
        "w_msg": _w((lambda *s: torch.randn(*s, dtype=torch.bfloat16) * 0.4)(2 * D + De, D)),
        "w_upd": _w((lambda *s: torch.randn(*s, dtype=torch.bfloat16) * 0.05)(2 * D, D)),
    }

def reference(x, e_attr, src, dst, w_msg, w_upd):
    N, D = x.shape
    m_in = torch.concatenate([x[src], x[dst], e_attr], axis=-1)
    msg = _silu(m_in @ w_msg)
    agg = _segment_sum(msg, dst, N)
    return _silu(torch.concatenate([x, agg], axis=-1) @ w_upd)
```

```cpp
#include <cuda_runtime.h>
#include <cuda.h>
#include <cuda_bf16.h>
#include <stdint.h>
#include <stddef.h>

#define ROTATE 1
#define W3REG 6

namespace {

constexpr int NN = 10000;
constexpr int EE = 160000;
constexpr int NCTA = 132;
constexpr int NPC = 76;
constexpr int NWR = 125;
constexpr int EPC = 1280;
constexpr int THREADS = 512;
constexpr int MCAP = 31;
constexpr int SCHUNK = NCTA * 8;
constexpr int RCHUNK = 128 * 8;
constexpr int CAP = 2048;
constexpr int NSPILL = NWR * MCAP - CAP;
#define PF1 0

static_assert(NCTA * NPC >= NN, "nodes");
static_assert(NWR * EPC == EE, "edges");
static_assert(NN <= 16384 && EPC < 2047 && NPC < 80, "entry packing");

constexpr int SLOT = 5120;
constexpr int SM_RING = 0;
constexpr int SM_W12 = 0;
constexpr int SM_WOFF = 65536;
constexpr int SM_OUT = 0;
constexpr int SM_EXT = 0;
constexpr int SM_AGG = 16 * SLOT;
constexpr int SM_WU = SM_AGG + 20480;
constexpr int SM_X = SM_WU + 65536;
constexpr int SM_Q = SM_X + 20480;
constexpr int SM_LIST = SM_Q + 20480;
constexpr int LISTB = (CAP + 64) * 4;
constexpr int SM_EID = SM_LIST + LISTB;
constexpr int SM_W3F = SM_EID + LISTB;
constexpr int SM_MISC = SM_W3F + 4096;
constexpr int SM_TOTAL = SM_MISC + 2048;
constexpr int SM_ALLOC = SM_TOTAL;
static_assert(2 * LISTB >= SCHUNK * 16, "staging");
static_assert(SM_ALLOC <= 232448, "smem");

struct Misc {
    int cnt[NCTA];
    int ncnt[128];
    int off[100];
    int ovf;
    int anyovf;
    int total;
    int pad;
    int wovf[128];
    uint4 trash;
    unsigned long long mbar[2];
};
constexpr int MISC_ZERO16 = 124;
static_assert(offsetof(Misc, mbar) == MISC_ZERO16 * 16, "misc layout");
static_assert(sizeof(Misc) <= 2048, "misc");

struct Scratch {
    uint4 P[NN * 16];
    uint4 mail[NCTA * RCHUNK];
    uint2 ovf[NWR * EPC];
    uint2 spill[NCTA * NSPILL];
    unsigned sync[64];
};
__device__ Scratch g_sc;

#define TSTAMP(i) do {} while (0)

__device__ __forceinline__ uint32_t smem_u32(const void* p) { return (uint32_t)__cvta_generic_to_shared(p); }

template <int ROWS>
__device__ __forceinline__ uint32_t sw(int row, int chunk) {
    return (uint32_t)((chunk >> 3) * (ROWS * 128) + row * 128 + (((chunk & 7) ^ (row & 7)) << 4));
}

__device__ __forceinline__ void cp16(uint32_t dst, const void* src) {
    asm volatile("cp.async.cg.shared.global [%0], [%1], 16;" ::"r"(dst), "l"(src) : "memory");
}
__device__ __forceinline__ void cp16z(uint32_t dst, const void* src, int bytes) {
    asm volatile("cp.async.cg.shared.global [%0], [%1], 16, %2;" ::"r"(dst), "l"(src), "r"(bytes) : "memory");
}
__device__ __forceinline__ void cp16i(uint32_t dst, const void* src, int skip) {
    asm volatile("{.reg .pred p; setp.eq.s32 p, %2, 0; @p cp.async.cg.shared.global [%0], [%1], 16;}" ::"r"(dst), "l"(src), "r"(skip) : "memory");
}
__device__ __forceinline__ void cp_commit() { asm volatile("cp.async.commit_group;" ::: "memory"); }
template <int N>
__device__ __forceinline__ void cp_wait() { asm volatile("cp.async.wait_group %0;" ::"n"(N) : "memory"); }
template <int ID, int N>
__device__ __forceinline__ void bar_sync() { asm volatile("bar.sync %0, %1;" ::"n"(ID), "n"(N) : "memory"); }
template <int ID, int N>
__device__ __forceinline__ void bar_arrive() { asm volatile("bar.arrive %0, %1;" ::"n"(ID), "n"(N) : "memory"); }
__device__ __forceinline__ void fence_async() { asm volatile("fence.proxy.async.shared::cta;" ::: "memory"); }

__device__ __forceinline__ void ldsm4t(uint32_t (&r)[4], uint32_t a) {
    asm volatile("ldmatrix.sync.aligned.m8n8.x4.trans.shared.b16 {%0,%1,%2,%3}, [%4];"
                 : "=r"(r[0]), "=r"(r[1]), "=r"(r[2]), "=r"(r[3]) : "r"(a));
}
__device__ __forceinline__ uint4 lds128(uint32_t a) {
    uint4 v;
    asm volatile("ld.shared.v4.u32 {%0,%1,%2,%3}, [%4];" : "=r"(v.x), "=r"(v.y), "=r"(v.z), "=r"(v.w) : "r"(a));
    return v;
}
__device__ __forceinline__ uint2 lds64(uint32_t a) {
    uint2 v;
    asm volatile("ld.shared.v2.u32 {%0,%1}, [%2];" : "=r"(v.x), "=r"(v.y) : "r"(a));
    return v;
}
__device__ __forceinline__ uint32_t lds32(uint32_t a) {
    uint32_t v;
    asm volatile("ld.shared.u32 %0, [%1];" : "=r"(v) : "r"(a));
    return v;
}
__device__ __forceinline__ uint32_t lds16(uint32_t a) {
    uint32_t v;
    asm volatile("ld.shared.u16 %0, [%1];" : "=r"(v) : "r"(a));
    return v;
}
__device__ __forceinline__ void sts32(uint32_t a, uint32_t v) {
    asm volatile("st.shared.u32 [%0], %1;" ::"r"(a), "r"(v) : "memory");
}
__device__ __forceinline__ void stsm4t(uint32_t a, uint32_t r0, uint32_t r1, uint32_t r2, uint32_t r3) {
    asm volatile("stmatrix.sync.aligned.m8n8.x4.trans.shared.b16 [%0], {%1,%2,%3,%4};"
                 ::"r"(a), "r"(r0), "r"(r1), "r"(r2), "r"(r3) : "memory");
}
__device__ __forceinline__ void mma16(float (&d)[4], const uint32_t a0, const uint32_t a1, const uint32_t a2,
                                      const uint32_t a3, const uint32_t b0, const uint32_t b1) {
    asm("mma.sync.aligned.m16n8k16.row.col.f32.bf16.bf16.f32 {%0,%1,%2,%3}, {%4,%5,%6,%7}, {%8,%9}, {%0,%1,%2,%3};"
        : "+f"(d[0]), "+f"(d[1]), "+f"(d[2]), "+f"(d[3])
        : "r"(a0), "r"(a1), "r"(a2), "r"(a3), "r"(b0), "r"(b1));
}
__device__ __forceinline__ uint32_t pack2(float lo, float hi) {
    uint32_t r;
    asm("cvt.rn.bf16x2.f32 %0, %1, %2;" : "=r"(r) : "f"(hi), "f"(lo));
    return r;
}
__device__ __forceinline__ uint32_t add2(uint32_t a, uint32_t b) {
    uint32_t r;
    asm("add.rn.bf16x2 %0, %1, %2;" : "=r"(r) : "r"(a), "r"(b));
    return r;
}
__device__ __forceinline__ float tanh_fast(float x) {
    float t;
    asm("tanh.approx.f32 %0, %1;" : "=f"(t) : "f"(x));
    return t;
}
__device__ __forceinline__ float silu_h(float h) { return fmaf(h, tanh_fast(h), h); }

__device__ __forceinline__ uint4 ld_relaxed128(const void* p) {
    uint4 v;
    asm volatile("ld.relaxed.gpu.global.v4.u32 {%0,%1,%2,%3}, [%4];" : "=r"(v.x), "=r"(v.y), "=r"(v.z), "=r"(v.w) : "l"(p) : "memory");
    return v;
}
__device__ __forceinline__ unsigned ld_relaxed32(const void* p) {
    unsigned v;
    asm volatile("ld.relaxed.gpu.global.u32 %0, [%1];" : "=r"(v) : "l"(p) : "memory");
    return v;
}
__device__ __forceinline__ void st_relaxed128(void* p, uint4 v) {
    asm volatile("st.relaxed.gpu.global.v4.u32 [%0], {%1,%2,%3,%4};" ::"l"(p), "r"(v.x), "r"(v.y), "r"(v.z), "r"(v.w) : "memory");
}
__device__ __forceinline__ uint32_t atoms_inc(uint32_t addr) {
    uint32_t r;
    asm volatile("atom.shared.add.u32 %0, [%1], 1;" : "=r"(r) : "r"(addr) : "memory");
    return r;
}
__device__ __forceinline__ void tma2d(uint32_t dst, const CUtensorMap* tm, int c0, int c1, uint32_t bar) {
    asm volatile("cp.async.bulk.tensor.2d.shared::cluster.global.mbarrier::complete_tx::bytes [%0], [%1, {%3, %4}], [%2];"
                 ::"r"(dst), "l"(tm), "r"(bar), "r"(c0), "r"(c1) : "memory");
}
__device__ __forceinline__ void mbar_wait(uint32_t bar) {
    uint32_t ok;
    int sp = 0;
    do {
        asm volatile("{.reg .pred p; mbarrier.try_wait.parity.shared.b64 p, [%1], 0; selp.u32 %0, 1, 0, p;}" : "=r"(ok) : "r"(bar) : "memory");
    } while (!ok && ++sp < (1 << 22));
}
template <int N>
__device__ __forceinline__ void cp_rows(uint32_t dst, const void* src) {
#pragma unroll
    for (int i = 0; i < N; i++)
        asm volatile("cp.async.cg.shared.global [%0], [%1], 16;" ::"r"(dst + i * 2048), "l"((const char*)src + i * 4096) : "memory");
}

#define ACC40(d)                                                                                              \
    "+f"(d[0]), "+f"(d[1]), "+f"(d[2]), "+f"(d[3]), "+f"(d[4]), "+f"(d[5]), "+f"(d[6]), "+f"(d[7]),         \
    "+f"(d[8]), "+f"(d[9]), "+f"(d[10]), "+f"(d[11]), "+f"(d[12]), "+f"(d[13]), "+f"(d[14]), "+f"(d[15]),   \
    "+f"(d[16]), "+f"(d[17]), "+f"(d[18]), "+f"(d[19]), "+f"(d[20]), "+f"(d[21]), "+f"(d[22]), "+f"(d[23]), \
    "+f"(d[24]), "+f"(d[25]), "+f"(d[26]), "+f"(d[27]), "+f"(d[28]), "+f"(d[29]), "+f"(d[30]), "+f"(d[31]), \
    "+f"(d[32]), "+f"(d[33]), "+f"(d[34]), "+f"(d[35]), "+f"(d[36]), "+f"(d[37]), "+f"(d[38]), "+f"(d[39])

template <int ACCUM>
__device__ __forceinline__ void wgmma_issue(float (&d)[40], uint32_t w_addr, uint32_t t_addr) {
    const uint32_t la = (w_addr >> 4) | 0x10000u, lb = (t_addr >> 4) | 0x10000u;
    asm volatile("wgmma.fence.sync.aligned;" ::: "memory");
#pragma unroll
    for (int ks = 0; ks < 8; ks++) {
        asm volatile(
            "{.reg .b64 da, db; .reg .pred p;\n"
            "setp.ne.s32 p, %43, 0;\n"
            "mov.b64 da, {%40, %42};\n"
            "mov.b64 db, {%41, %42};\n"
            "wgmma.mma_async.sync.aligned.m64n80k16.f32.bf16.bf16 "
            "{%0,%1,%2,%3,%4,%5,%6,%7,%8,%9,%10,%11,%12,%13,%14,%15,%16,%17,%18,%19,"
            "%20,%21,%22,%23,%24,%25,%26,%27,%28,%29,%30,%31,%32,%33,%34,%35,%36,%37,%38,%39},"
            "da, db, p, 1, 1, 1, 0;}"
            : ACC40(d)
            : "r"(la + ks * 128), "r"(lb + (ks >> 2) * 640 + (ks & 3) * 2), "r"(0x40000040u), "r"((ks > 0 || ACCUM) ? 1 : 0));
    }
    asm volatile("wgmma.commit_group.sync.aligned;" ::: "memory");
}
template <int N>
__device__ __forceinline__ void wgmma_wait(float (&d)[40]) {
    asm volatile("wgmma.wait_group.sync.aligned %40;" : ACC40(d) : "n"(N) : "memory");
}
__device__ __forceinline__ void store_tile_half(uint32_t a, const float (&d)[40]) {
#pragma unroll
    for (int j = 0; j < 10; j += 2)
        stsm4t(a + j * 1024, pack2(0.5f * d[4 * j], 0.5f * d[4 * j + 1]), pack2(0.5f * d[4 * j + 2], 0.5f * d[4 * j + 3]),
               pack2(0.5f * d[4 * j + 4], 0.5f * d[4 * j + 5]), pack2(0.5f * d[4 * j + 6], 0.5f * d[4 * j + 7]));
}

template <int MODE>
__global__ void __launch_bounds__(THREADS, 1)
mpnn_kernel(const __nv_bfloat16* __restrict__ x, const __nv_bfloat16* __restrict__ e_attr,
            const int* __restrict__ src, const int* __restrict__ dst,
            const __nv_bfloat16* __restrict__ w_msg,
            __nv_bfloat16* __restrict__ out, Scratch* __restrict__ sc,
            const __grid_constant__ CUtensorMap tm_wm, const __grid_constant__ CUtensorMap tm_wu,
            const __grid_constant__ CUtensorMap tm_mail, const __grid_constant__ CUtensorMap tm_p) {
    extern __shared__ __align__(1024) uint8_t smem[];
    const uint32_t sb = smem_u32(smem);
    Misc* ms = reinterpret_cast<Misc*>(smem + SM_MISC);
    const unsigned tid = threadIdx.x, lane = tid & 31;
    __builtin_assume(tid < THREADS);
    const int warp = __shfl_sync(0xffffffffu, tid >> 5, 0);
    const unsigned cta = blockIdx.x;
    __builtin_assume(cta < NCTA);
    if (tid == 0) TSTAMP(0);

    const unsigned g = lane >> 2, q = lane & 3;
    const int node0 = cta * NPC;
    const uint32_t tile_a = sw<80>(((lane >> 4) & 1) * 8 + (lane & 7), (warp & 7) * 2 + ((lane >> 3) & 1));

    if (warp >= 8) {
        const unsigned tb = tid - 256;
        __builtin_assume(tb < 256);
        const bool writer = (MODE & 1) && cta < NWR;
        uint32_t dv[5], sv[5];
        if (writer) {
            const int* dp = dst + cta * EPC;
            const int* sp = src + cta * EPC;
            asm volatile("ld.global.nc.v4.u32 {%0,%1,%2,%3}, [%4];" : "=r"(dv[0]), "=r"(dv[1]), "=r"(dv[2]), "=r"(dv[3]) : "l"(dp + tb * 4));
            asm volatile("ld.global.nc.u32 %0, [%1];" : "=r"(dv[4]) : "l"(dp + 1024 + tb));
            asm volatile("ld.global.nc.v4.u32 {%0,%1,%2,%3}, [%4];" : "=r"(sv[0]), "=r"(sv[1]), "=r"(sv[2]), "=r"(sv[3]) : "l"(sp + tb * 4));
            asm volatile("ld.global.nc.u32 %0, [%1];" : "=r"(sv[4]) : "l"(sp + 1024 + tb));
        }
        bar_arrive<3, 512>();
        unsigned htarget = 0;
        if (tb == 0 && MODE == 3) htarget = ld_relaxed32(&sc->sync[32]);
        if (tb == 32) asm volatile("prefetch.tensormap [%0];" ::"l"(&tm_mail) : "memory");
        if (tb < MISC_ZERO16) reinterpret_cast<uint4*>(ms)[tb] = make_uint4(0, 0, 0, 0);
        bar_sync<2, 256>();
        if (tb == 0) TSTAMP(17);
        if (writer) {
            uint32_t own[5], pos[5];
#pragma unroll
            for (int i = 0; i < 5; i++) {
                own[i] = (dv[i] * 55189u) >> 22;
                pos[i] = atoms_inc(sb + SM_MISC + own[i] * 4);
            }
            if (tb == 0) TSTAMP(18);
            uint32_t pmax = 0;
#pragma unroll
            for (int i = 0; i < 5; i++) {
                const uint32_t nl = dv[i] - own[i] * NPC;
                const uint32_t el1 = i < 4 ? tb * 4 + i + 1 : tb + 1025;
                sts32(sb + SM_LIST + own[i] * 128 + (pos[i] < MCAP ? pos[i] * 4 + 4 : 0), (sv[i] * 128u + nl) * 2048u + el1);
                pmax = max(pmax, pos[i]);
            }
            if (pmax >= MCAP) {
#pragma unroll
                for (int i = 0; i < 5; i++) {
                    if (pos[i] >= MCAP) {
                        const int k = atomicAdd(&ms->ovf, 1);
                        sc->ovf[cta * EPC + k] = make_uint2(dv[i], cta * EPC + (i < 4 ? tb * 4 + i : tb + 1024));
                    }
                }
                __threadfence();
            }
            if (tb == 0) TSTAMP(8);
            bar_sync<2, 256>();
            if (tb == 0) TSTAMP(19);
            if (tb < NCTA) sts32(sb + SM_LIST + tb * 128, ((uint32_t)ms->ovf << 11) | (uint32_t)ms->cnt[tb]);
            fence_async();
            bar_sync<2, 256>();
            if (tb == 0) {
                asm volatile("cp.async.bulk.tensor.2d.global.shared::cta.bulk_group [%0, {%2, %3}], [%1];"
                             ::"l"(&tm_mail), "r"(sb + SM_LIST), "r"(cta * 32), "r"(0) : "memory");
                asm volatile("cp.async.bulk.commit_group;" ::: "memory");
                TSTAMP(9);
                asm volatile("cp.async.bulk.wait_group 0;" ::: "memory");
                TSTAMP(23);
            }
        }
        if (!(MODE & 2)) return;
        if (MODE == 3) {
            if (tb == 0) {
                asm volatile("red.relaxed.gpu.global.add.u32 [%0], 1;" ::"l"(&sc->sync[32]) : "memory");
                htarget = htarget - htarget % NCTA + NCTA;
                int sp = 0;
                while ((int)(ld_relaxed32(&sc->sync[32]) - htarget) < 0 && ++sp < (1 << 22)) {}
                TSTAMP(24);
            }
            bar_sync<2, 256>();
        }
        uint32_t w[2][8];
        {
            const uint4* mine = sc->mail + cta * RCHUNK + (tb >> 2) * 8 + (tb & 3);
            const uint4* mine2 = tb + 256 < NWR * 4 ? mine + 512 : mine;
            asm volatile("ld.relaxed.gpu.global.v4.u32 {%0,%1,%2,%3}, [%16];\n"
                         "ld.relaxed.gpu.global.v4.u32 {%8,%9,%10,%11}, [%17];\n"
                         "ld.relaxed.gpu.global.v4.u32 {%4,%5,%6,%7}, [%16+64];\n"
                         "ld.relaxed.gpu.global.v4.u32 {%12,%13,%14,%15}, [%17+64];"
                         : "=r"(w[0][0]), "=r"(w[0][1]), "=r"(w[0][2]), "=r"(w[0][3]), "=r"(w[0][4]), "=r"(w[0][5]), "=r"(w[0][6]), "=r"(w[0][7]),
                           "=r"(w[1][0]), "=r"(w[1][1]), "=r"(w[1][2]), "=r"(w[1][3]), "=r"(w[1][4]), "=r"(w[1][5]), "=r"(w[1][6]), "=r"(w[1][7])
                         : "l"(mine), "l"(mine2) : "memory");
        }
        uint32_t hd[2];
        hd[0] = __shfl_sync(0xffffffffu, w[0][0], lane & ~3u);
        hd[1] = __shfl_sync(0xffffffffu, w[1][0], lane & ~3u);
        if (tb + 256 >= NWR * 4) hd[1] = 0;
        if (tb == 0) TSTAMP(10);
        int lim[2];
#pragma unroll
        for (int b = 0; b < 2; b++) {
            if ((hd[b] & 0x7ffu) > MCAP) { ms->wovf[(tb >> 2) + 64 * b] = hd[b] >> 11; ms->anyovf = 1; }
            lim[b] = (int)(hd[b] & 0x7ffu) - (int)(tb & 3) * 4;
        }
        const bool second = __any_sync(0xffffffffu, max(lim[0], lim[1]) >= 16);
        const uint32_t dummy = (96u + lane) << 11;
        if ((tb & 3) == 0) w[0][0] = w[1][0] = dummy;
        uint32_t rk[2][8];
        const uint32_t nc = smem_u32(ms->ncnt);
        auto hist = [&](int i0) {
#pragma unroll
            for (int b = 0; b < 2; b++)
#pragma unroll
                for (int i = i0; i < i0 + 4; i++) {
                    w[b][i] = lim[b] >= (i & 3) + (i >> 2) * 16 ? w[b][i] : dummy;
                    rk[b][i] = atoms_inc(nc + ((w[b][i] >> 9) & 0x1fc));
                }
        };
        hist(0);
        if (second) hist(4);
        const uint32_t wo = sb + SM_WOFF + (warp - 8) * 512;
        sts32(wo + 384 + lane * 4, 1u << 20);
        if (tb == 0) TSTAMP(20);
        bar_sync<2, 256>();
        if (tb == 0) TSTAMP(21);
        int total;
        {
            const int c0 = lds32(nc + lane * 12), c1 = lds32(nc + lane * 12 + 4), c2 = lds32(nc + lane * 12 + 8);
            int s = c0 + c1 + c2;
#pragma unroll
            for (int d = 1; d < 32; d <<= 1) {
                const int t = __shfl_up_sync(0xffffffffu, s, d);
                if (lane >= d) s += t;
            }
            sts32(wo + lane * 12, s - c2 - c1 - c0);
            sts32(wo + lane * 12 + 4, s - c2 - c1);
            sts32(wo + lane * 12 + 8, s - c2);
            total = __shfl_sync(0xffffffffu, s, 31);
            if (warp == 15) {
                ms->off[lane * 3] = min(s - c2 - c1 - c0, CAP);
                ms->off[lane * 3 + 1] = min(s - c2 - c1, CAP);
                ms->off[lane * 3 + 2] = min(s - c2, CAP);
                if (lane == 31) { ms->off[96] = min(s, CAP); ms->total = s; if (s > CAP) ms->anyovf = 1; }
                if (total < CAP) {
                    const uint32_t pa = sb + SM_LIST + (total + lane) * 4;
                    sts32(pa, (79u * 128u + 7u * 16u) << 16);
                    sts32(pa + LISTB, 0u);
                    if (lane < 16) sts32(pa + 128, (79u * 128u + 7u * 16u) << 16);
                }
            }
            __syncwarp();
        }
        if (tb == 0) TSTAMP(22);
        const uint32_t eb = (tb >> 2) * EPC - 1;
        auto scatter = [&](int i0) {
#pragma unroll
            for (int b = 0; b < 2; b++)
#pragma unroll
                for (int i = i0; i < i0 + 4; i++) rk[b][i] += lds32(wo + ((w[b][i] >> 9) & 0x1fc));
#pragma unroll
            for (int b = 0; b < 2; b++)
#pragma unroll
                for (int i = i0; i < i0 + 4; i++) {
                    const uint32_t a = sb + SM_LIST + min(rk[b][i], (uint32_t)(CAP + 63)) * 4;
                    sts32(a, (w[b][i] >> 18) | ((w[b][i] << 12) & 0x3f800000u) | ((w[b][i] << 9) & 0x700000u));
                    sts32(a + LISTB, eb + b * (64 * EPC) + (w[b][i] & 0x7ff));
                }
            if (total > CAP) {
#pragma unroll
                for (int b = 0; b < 2; b++)
#pragma unroll
                    for (int i = i0; i < i0 + 4; i++)
                        if (rk[b][i] >= CAP && rk[b][i] < (1u << 20))
                            sc->spill[cta * NSPILL + rk[b][i] - CAP] = make_uint2(node0 + ((w[b][i] >> 11) & 127), eb + b * (64 * EPC) + (w[b][i] & 0x7ff));
            }
        };
        scatter(0);
        if (second) scatter(4);
        if (tb == 0) TSTAMP(11);
    } else {
        const uint32_t mb = smem_u32(ms->mbar);
        const char* epf = reinterpret_cast<const char*>(e_attr) + (size_t)cta * (EPC * 32);
        {
            const unsigned r0 = tid >> 4, c0 = tid & 15;
            bar_sync<3, 512>();
            cp_rows<8>(sb + SM_W12 + sw<256>(r0, c0), reinterpret_cast<const uint4*>(w_msg) + tid);
            const uint32_t dx = sb + SM_X + sw<80>(r0, c0);
            const uint4* xg = reinterpret_cast<const uint4*>(x) + c0;
#pragma unroll
            for (int i = 0; i < 5; i++) cp16(dx + i * 2048, xg + min(node0 + r0 + i * 16, (unsigned)(NN - 1)) * 16);
            cp_commit();
        }
        unsigned target = 0;
        if (tid == 32) asm volatile("prefetch.tensormap [%0];" ::"l"(&tm_p) : "memory");
        if (tid == 64) asm volatile("prefetch.tensormap [%0];" ::"l"(&tm_wu) : "memory");
        if (tid == 0) {
            if (MODE == 3) target = ld_relaxed32(&sc->sync[0]);
            asm volatile("mbarrier.init.shared.b64 [%0], 1;" ::"r"(mb) : "memory");
            asm volatile("mbarrier.init.shared.b64 [%0], 1;" ::"r"(mb + 8) : "memory");
            asm volatile("fence.mbarrier_init.release.cluster;" ::: "memory");
            asm volatile("mbarrier.arrive.expect_tx.shared.b64 _, [%0], %1;" ::"r"(mb), "n"(32768) : "memory");
            tma2d(sb + SM_W12 + 16384, &tm_wm, 0, 128, mb);
            tma2d(sb + SM_W12 + 32768 + 16384, &tm_wm, 64, 128, mb);
            if (PF1 > 0 && cta < NWR)
                asm volatile("cp.async.bulk.prefetch.L2.global [%0], %1;" ::"l"(epf), "n"(PF1 > 0 ? PF1 : 16) : "memory");
        }
        const int wg = warp >> 2;
        float a0[40];
        cp_wait<0>();
        fence_async();
        bar_sync<1, 256>();
        if (tid == 0) TSTAMP(1);
        wgmma_issue<0>(a0, sb + SM_W12 + wg * 32768, sb + SM_X);
        unsigned short w3v[8];
        {
            const unsigned short* w3 = reinterpret_cast<const unsigned short*>(w_msg) + (256 + 4 * q) * 128 + warp * 16 + g;
#pragma unroll
            for (int i = 0; i < 4; i++) {
                asm volatile("ld.global.u16 %0, [%1];" : "=h"(w3v[i]) : "l"(w3 + i * 128) : "memory");
                asm volatile("ld.global.u16 %0, [%1];" : "=h"(w3v[4 + i]) : "l"(w3 + i * 128 + 8) : "memory");
            }
        }
        wgmma_wait<0>(a0);
        if (tid == 0) TSTAMP(15);
        store_tile_half(sb + SM_AGG + tile_a, a0);
        fence_async();
        bar_sync<1, 256>();
        if (tid == 0) TSTAMP(16);
        if (tid == 0) {
            if (MODE & 1) {
                asm volatile("cp.async.bulk.tensor.2d.global.shared::cta.bulk_group [%0, {%2, %3}], [%1];"
                             ::"l"(&tm_p), "r"(sb + SM_AGG), "r"(0), "r"(node0) : "memory");
                asm volatile("cp.async.bulk.tensor.2d.global.shared::cta.bulk_group [%0, {%2, %3}], [%1];"
                             ::"l"(&tm_p), "r"(sb + SM_AGG + 10240), "r"(64), "r"(node0) : "memory");
                asm volatile("cp.async.bulk.commit_group;" ::: "memory");
            }
            if (MODE & 2) {
                asm volatile("mbarrier.arrive.expect_tx.shared.b64 _, [%0], %1;" ::"r"(mb + 8), "n"(65536) : "memory");
                tma2d(sb + SM_WU, &tm_wu, 0, 0, mb + 8);
                tma2d(sb + SM_WU + 32768, &tm_wu, 64, 0, mb + 8);
            }
            if (PF1 < EPC * 32 && cta < NWR)
                asm volatile("cp.async.bulk.prefetch.L2.global [%0], %1;" ::"l"(epf + PF1), "n"(PF1 < EPC * 32 ? EPC * 32 - PF1 : 16) : "memory");
        }
        mbar_wait(mb);
        wgmma_issue<0>(a0, sb + SM_W12 + wg * 32768 + 16384, sb + SM_X);
        wgmma_wait<0>(a0);
        if (!(MODE & 2)) {
            asm volatile("cp.async.bulk.wait_group 0;" ::: "memory");
            return;
        }
        if (tid == 0) TSTAMP(25);
        store_tile_half(sb + SM_Q + tile_a, a0);
        {
            const __nv_bfloat162 hf = __floats2bfloat162_rn(0.5f, 0.5f);
            uint32_t f[4] = {w3v[0] | ((uint32_t)w3v[1] << 16), w3v[4] | ((uint32_t)w3v[5] << 16),
                             w3v[2] | ((uint32_t)w3v[3] << 16), w3v[6] | ((uint32_t)w3v[7] << 16)};
#pragma unroll
            for (int i = 0; i < 4; i++) {
                __nv_bfloat162 h = __hmul2(*reinterpret_cast<__nv_bfloat162*>(&f[i]), hf);
                f[i] = *reinterpret_cast<uint32_t*>(&h);
            }
            reinterpret_cast<uint4*>(smem + SM_W3F)[tid] = make_uint4(f[0], f[1], f[2], f[3]);
        }
        if (tid == 0 && MODE == 3) {
            TSTAMP(4);
            asm volatile("cp.async.bulk.wait_group 0;" ::: "memory");
            TSTAMP(2);
            asm volatile("red.relaxed.gpu.global.add.u32 [%0], 1;" ::"l"(&sc->sync[0]) : "memory");
            TSTAMP(3);
            target = target - target % NCTA + NCTA;
            int sp = 0;
            while ((int)(ld_relaxed32(&sc->sync[0]) - target) < 0 && ++sp < (1 << 22)) {}
            TSTAMP(5);
        }
    }
    __syncthreads();
    if (tid == 0) TSTAMP(6);
    const int nvalid = min(NPC, NN - node0);

    const int M = ms->off[96];
    const int T = (M + 15) >> 4;
    const int s = ((warp * T) >> 4) * 16;
    const int e = min((((warp + 1) * T) >> 4) * 16, M);
    const uint32_t ring = sb + SM_RING + warp * SLOT;
    {
        const unsigned fr = lane >> 3, fc = lane & 7;
        const char* Pb0 = reinterpret_cast<const char*>(sc->P) + ((fc ^ fr) << 4);
        const char* Pb1 = reinterpret_cast<const char*>(sc->P) + ((fc ^ fr ^ 4) << 4);
        const char* Eb = reinterpret_cast<const char*>(e_attr) + (lane & 1) * 16;
        const uint32_t fdst = ring + lane * 16;
        const uint32_t la = ring + (lane & 7) * 128 + (((lane >> 3) ^ (lane & 7)) << 4);
        const uint32_t w3a = sb + SM_W3F + lane * 16;
        uint32_t sn[4], ei;
        auto fidx = [&](int tb) {
#pragma unroll
            for (int i = 0; i < 4; i++) sn[i] = lds16(sb + SM_LIST + (tb + fr) * 4 + i * 16);
            ei = lds32(sb + SM_EID + (tb + (lane >> 1)) * 4);
        };
        auto fetchP = [&](int h, int skip) {
#pragma unroll
            for (int i = 0; i < 4; i++) cp16i(fdst + h * 2048 + i * 512, ((i & 1) ? Pb1 : Pb0) + (size_t)sn[i] * 256 + h * 128, skip);
        };
        auto fetchE = [&](int skip) { cp16i(fdst + 4096, Eb + (size_t)ei * 32, skip); };
        uint4 w3r[W3REG > 0 ? W3REG : 1];
        int lo = s;
        while (lo < e) {
            int tb = lo & ~15;
            fidx(tb);
            fetchE(0);
            fetchP(0, 0);
            cp_commit();
            const int nb = lds32(sb + SM_LIST + lo * 4) >> 23;
            const int hi = min(e, ms->off[min(nb + 8, 96)]);
            const int o0 = ms->off[nb + g];
            const uint32_t cnt = ms->off[nb + g + 1] - o0;
#pragma unroll
            for (int m = 0; m < W3REG; m++) w3r[m] = lds128(w3a + m * 512);
            float acc[8][4];
#pragma unroll
            for (int m = 0; m < 8; m++)
#pragma unroll
                for (int k = 0; k < 4; k++) acc[m][k] = 0.f;
            fetchP(1, 0);
            cp_commit();
            uint32_t qa0, qa1, ss0, ss1;
            uint2 e0, e1;
            int last;
            float c[2][2][2][4];
            auto top = [&]() {
                qa0 = sb + SM_Q + (lds16(sb + SM_LIST + (tb + (lane & 7)) * 4 + 2) ^ ((lane >> 3) << 4));
                qa1 = sb + SM_Q + (lds16(sb + SM_LIST + (tb + (lane & 7)) * 4 + 34) ^ ((lane >> 3) << 4));
                tb += 16;
                fidx(tb);
                cp_wait<1>();
                __syncwarp();
                e0 = lds64(ring + 4096 + lane * 8);
                e1 = lds64(ring + 4096 + 256 + lane * 8);
            };
            auto stageA = [&](int j, float (&cc)[2][2][4]) {
                if (j == 2) { cp_wait<1>(); __syncwarp(); }
                uint32_t p0[4], p1[4], r0[4], r1[4];
                ldsm4t(p0, (la ^ ((j & 1) << 6)) + (j >> 1) * 2048);
                ldsm4t(p1, (la ^ ((j & 1) << 6)) + (j >> 1) * 2048 + 1024);
                ldsm4t(r0, (qa0 ^ ((j & 1) << 6)) + (j >> 1) * 10240);
                ldsm4t(r1, (qa1 ^ ((j & 1) << 6)) + (j >> 1) * 10240);
#pragma unroll
                for (int i = 0; i < 4; i++) { p0[i] = add2(p0[i], r0[i]); p1[i] = add2(p1[i], r1[i]); }
#pragma unroll
                for (int mm = 0; mm < 2; mm++) {
                    const int m = 2 * j + mm;
                    const uint4 wf = m < W3REG ? w3r[m < W3REG ? m : 0] : lds128(w3a + m * 512);
                    cc[mm][0][0] = __uint_as_float(p0[2 * mm] << 16); cc[mm][0][1] = __uint_as_float(p0[2 * mm] & 0xffff0000u);
                    cc[mm][0][2] = __uint_as_float(p0[2 * mm + 1] << 16); cc[mm][0][3] = __uint_as_float(p0[2 * mm + 1] & 0xffff0000u);
                    cc[mm][1][0] = __uint_as_float(p1[2 * mm] << 16); cc[mm][1][1] = __uint_as_float(p1[2 * mm] & 0xffff0000u);
                    cc[mm][1][2] = __uint_as_float(p1[2 * mm + 1] << 16); cc[mm][1][3] = __uint_as_float(p1[2 * mm + 1] & 0xffff0000u);
                    mma16(cc[mm][0], wf.x, wf.y, wf.z, wf.w, e0.x, e0.y);
                    mma16(cc[mm][1], wf.x, wf.y, wf.z, wf.w, e1.x, e1.y);
                }
                if (j & 1) {
                    __syncwarp();
                    if (j == 1) fetchE(last);
                    fetchP(j >> 1, last);
                    cp_commit();
                }
            };
            auto stageB = [&](int j, float (&cc)[2][2][4]) {
#pragma unroll
                for (int mm = 0; mm < 2; mm++) {
                    const uint32_t a0 = pack2(silu_h(cc[mm][0][0]), silu_h(cc[mm][0][1]));
                    const uint32_t a1 = pack2(silu_h(cc[mm][0][2]), silu_h(cc[mm][0][3]));
                    const uint32_t a2 = pack2(silu_h(cc[mm][1][0]), silu_h(cc[mm][1][1]));
                    const uint32_t a3 = pack2(silu_h(cc[mm][1][2]), silu_h(cc[mm][1][3]));
                    mma16(acc[2 * j + mm], a0, a1, a2, a3, ss0, ss1);
                }
            };
            top();
            stageA(0, c[0]);
#pragma unroll 1
            for (;;) {
                const uint32_t u = tb - 16 + 2 * q - o0;
                ss0 = (u < cnt ? 0x3F80u : 0u) | (u + 1 < cnt ? 0x3F800000u : 0u);
                ss1 = (u + 8 < cnt ? 0x3F80u : 0u) | (u + 9 < cnt ? 0x3F800000u : 0u);
                last = tb >= hi;
                stageA(1, c[1]); stageB(0, c[0]);
                stageA(2, c[0]); stageB(1, c[1]);
                stageA(3, c[1]); stageB(2, c[0]);
                top();
                stageA(0, c[0]);
                stageB(3, c[1]);
                if (last) break;
            }
            {
                const int nd = nb + (lane & 7);
                const int p0 = ms->off[nd], p1 = ms->off[nd + 1];
                const bool full = p0 >= s && p1 <= e && p1 > p0;
                const uint32_t aa = sb + SM_AGG + sw<80>(nd, lane >> 3);
#pragma unroll
                for (int j = 0; j < 4; j++) {
                    const uint32_t a = full ? (aa ^ ((j & 1) << 6)) + (j >> 1) * 10240 : smem_u32(&ms->trash);
                    stsm4t(a, pack2(acc[2 * j][0], acc[2 * j][1]), pack2(acc[2 * j][2], acc[2 * j][3]),
                           pack2(acc[2 * j + 1][0], acc[2 * j + 1][1]), pack2(acc[2 * j + 1][2], acc[2 * j + 1][3]));
                }
            }
#pragma unroll
            for (int b = 0; b < 2; b++) {
                const int nd = nb + 2 * q + b;
                const int p0 = ms->off[nd], p1 = ms->off[nd + 1];
                const bool fst = p0 < s && p1 > s;
                const bool lst = p0 >= s && p0 < e && p1 > e;
                if (fst || lst) {
                    float* pp = reinterpret_cast<float*>(smem + SM_RING + warp * SLOT + (fst ? 4608 : 0)) + g;
#pragma unroll
                    for (int m = 0; m < 8; m++) {
                        pp[m * 16] = acc[m][b];
                        pp[m * 16 + 8] = acc[m][2 + b];
                    }
                }
            }
            __syncwarp();
            lo = hi;
        }
        {
            const int nd = warp * 5 + min(lane, 4u);
            unsigned em = __ballot_sync(0xffffffffu, ms->off[nd] == ms->off[nd + 1]) & 31u;
            while (em) {
                const int k = __ffs(em) - 1;
                em &= em - 1;
                *reinterpret_cast<uint2*>(smem + SM_AGG + sw<80>(warp * 5 + k, lane >> 1) + (lane & 1) * 8) = make_uint2(0, 0);
            }
        }
    }
    if (tid == 0) TSTAMP(7);
    fence_async();
    __syncthreads();
    if (warp >= 8) {
        const int tb = tid - 256;
#pragma unroll 1
        for (int w1 = warp - 8; w1 < 16; w1 += 8) {
            const int s1 = ((w1 * T) >> 4) * 16;
            const int e1 = min((((w1 + 1) * T) >> 4) * 16, M);
            if (s1 >= e1) continue;
            const int nl = reinterpret_cast<const uint32_t*>(smem + SM_LIST)[e1 - 1] >> 23;
            const int o0 = ms->off[nl], o1 = ms->off[nl + 1];
            if (o0 >= s1 && o1 > e1) {
                float4 v = reinterpret_cast<const float4*>(smem + SM_RING + w1 * SLOT)[lane];
                for (int w2 = w1 + 1; w2 < 16; w2++) {
                    const int s2 = ((w2 * T) >> 4) * 16;
                    const int e2 = min((((w2 + 1) * T) >> 4) * 16, M);
                    if (s2 >= o1) break;
                    if (s2 < e2) {
                        const float4 u = reinterpret_cast<const float4*>(smem + SM_RING + w2 * SLOT + 4608)[lane];
                        v.x += u.x; v.y += u.y; v.z += u.z; v.w += u.w;
                    }
                }
                *reinterpret_cast<uint2*>(smem + SM_AGG + sw<80>(nl, lane >> 1) + (lane & 1) * 8) =
                    make_uint2(pack2(v.x, v.y), pack2(v.z, v.w));
            }
        }
        if (ms->anyovf) {
            __threadfence();
            bar_sync<2, 256>();
            float* ext = reinterpret_cast<float*>(smem + SM_EXT);
            for (int i = tb; i < 80 * 128; i += 256) ext[i] = 0.f;
            bar_sync<2, 256>();
            const char* Pb = reinterpret_cast<const char*>(sc->P);
            for (int w = -1; w < NWR; w++) {
                const int cnt = w < 0 ? ms->total - CAP : ms->wovf[w];
                for (int k = warp - 8; k < cnt; k += 8) {
                    uint2 en;
                    const uint2* ep = w < 0 ? sc->spill + cta * NSPILL + k : sc->ovf + w * EPC + k;
                    asm volatile("ld.relaxed.gpu.global.v2.u32 {%0,%1}, [%2];" : "=r"(en.x), "=r"(en.y) : "l"(ep) : "memory");
                    const int nl = (int)en.x - node0;
                    const uint32_t eid = en.y;
                    if (nl < 0 || nl >= NPC) continue;
                    const uint32_t sn = src[eid];
                    for (int u = 0; u < 4; u++) {
                        const int f = lane * 4 + u;
                        float h = 0.f;
                        for (int kk = 0; kk < 16; kk++)
                            h = fmaf(__bfloat162float(e_attr[(size_t)eid * 16 + kk]), __bfloat162float(w_msg[(256 + kk) * 128 + f]), h);
                        h = 0.5f * h + __bfloat162float(*reinterpret_cast<const __nv_bfloat16*>(Pb + sn * 256 + f * 2)) +
                            __bfloat162float(*reinterpret_cast<const __nv_bfloat16*>(smem + SM_Q + sw<80>(nl, f >> 3) + (f & 7) * 2));
                        atomicAdd(&ext[nl * 128 + f], __bfloat162float(__float2bfloat16_rn(silu_h(h))));
                    }
                }
            }
            bar_sync<2, 256>();
            for (int i = tb; i < 80 * 128; i += 256) {
                const int r = i >> 7, f = i & 127;
                __nv_bfloat16* pp = reinterpret_cast<__nv_bfloat16*>(smem + SM_AGG + sw<80>(r, f >> 3) + (f & 7) * 2);
                *pp = __float2bfloat16_rn(__bfloat162float(*pp) + ext[i]);
            }
        }
        fence_async();
        bar_arrive<4, 512>();
        return;
    }
    {
        const int wg = warp >> 2;
        float a0[40];
        mbar_wait(smem_u32(ms->mbar) + 8);
        wgmma_issue<0>(a0, sb + SM_WU + wg * 32768, sb + SM_X);
        bar_sync<4, 512>();
        if (tid == 0) TSTAMP(14);
        wgmma_issue<1>(a0, sb + SM_WU + wg * 32768 + 16384, sb + SM_AGG);
        wgmma_wait<0>(a0);
        if (tid == 0) TSTAMP(26);
#pragma unroll
        for (int j = 0; j < 10; j += 2) {
            uint32_t r[4];
#pragma unroll
            for (int k = 0; k < 4; k++) r[k] = pack2(silu_h(0.5f * a0[4 * j + 2 * k]), silu_h(0.5f * a0[4 * j + 2 * k + 1]));
            stsm4t(sb + SM_OUT + tile_a + j * 1024, r[0], r[1], r[2], r[3]);
        }
        if (wg == 0) bar_sync<1, 128>(); else bar_sync<3, 128>();
        const int t = tid & 127;
        uint4* og = reinterpret_cast<uint4*>(out) + (size_t)node0 * 16 + wg * 8 + (t & 7);
#pragma unroll
        for (int i = 0; i < 5; i++) {
            const int row = (t >> 3) + i * 16;
            if (row < nvalid) og[row * 16] = *reinterpret_cast<const uint4*>(smem + SM_OUT + sw<80>(row, wg * 8 + (t & 7)));
        }
    }
    if (tid == 0) TSTAMP(12);
}

}

typedef CUresult (*EncodeFn)(CUtensorMap*, CUtensorMapDataType, cuuint32_t, void*, const cuuint64_t*, const cuuint64_t*,
                             const cuuint32_t*, const cuuint32_t*, CUtensorMapInterleave, CUtensorMapSwizzle,
                             CUtensorMapL2promotion, CUtensorMapFloatOOBfill);

static void make_map(EncodeFn enc, CUtensorMap* tm, const void* base, int rows, int box_rows) {
    const cuuint64_t dims[2] = {128, (cuuint64_t)rows};
    const cuuint64_t strides[1] = {256};
    const cuuint32_t box[2] = {64, (cuuint32_t)box_rows};
    const cuuint32_t estr[2] = {1, 1};
    enc(tm, CU_TENSOR_MAP_DATA_TYPE_BFLOAT16, 2, const_cast<void*>(base), dims, strides, box, estr, CU_TENSOR_MAP_INTERLEAVE_NONE,
        CU_TENSOR_MAP_SWIZZLE_128B, CU_TENSOR_MAP_L2_PROMOTION_NONE, CU_TENSOR_MAP_FLOAT_OOB_FILL_NONE);
}

extern "C" void kernel_launch(void* const* d_in, const int* in_sizes, int n_in, void* d_out, int out_size) {
    const __nv_bfloat16* x = (const __nv_bfloat16*)d_in[0];
    const __nv_bfloat16* e_attr = (const __nv_bfloat16*)d_in[1];
    const int* src = (const int*)d_in[2];
    const int* dst = (const int*)d_in[3];
    const __nv_bfloat16* w_msg = (const __nv_bfloat16*)d_in[4];
    __nv_bfloat16* out = (__nv_bfloat16*)d_out;

    static int fused = -1;
    static Scratch* sc = nullptr;
    static EncodeFn enc = nullptr;
    if (fused < 0) {
        cudaFuncSetAttribute(mpnn_kernel<1>, cudaFuncAttributeMaxDynamicSharedMemorySize, SM_ALLOC);
        cudaFuncSetAttribute(mpnn_kernel<2>, cudaFuncAttributeMaxDynamicSharedMemorySize, SM_ALLOC);
        cudaFuncSetAttribute(mpnn_kernel<3>, cudaFuncAttributeMaxDynamicSharedMemorySize, SM_ALLOC);
        int dev = 0, sms = 0, occ = 0;
        cudaGetDevice(&dev);
        cudaDeviceGetAttribute(&sms, cudaDevAttrMultiProcessorCount, dev);
        cudaOccupancyMaxActiveBlocksPerMultiprocessor(&occ, mpnn_kernel<3>, THREADS, SM_ALLOC);
        cudaGetSymbolAddress((void**)&sc, g_sc);
        cudaDriverEntryPointQueryResult qr;
        cudaGetDriverEntryPoint("cuTensorMapEncodeTiled", (void**)&enc, cudaEnableDefault, &qr);
        fused = (sms * occ >= NCTA) ? 1 : 0;
    }
    CUtensorMap tm_wm, tm_wu, tm_mail, tm_p;
    make_map(enc, &tm_p, sc->P, NN, NPC);
    {
        const cuuint64_t dims[2] = {RCHUNK * 4, NCTA};
        const cuuint64_t strides[1] = {RCHUNK * 16};
        const cuuint32_t box[2] = {32, NCTA};
        const cuuint32_t estr[2] = {1, 1};
        enc(&tm_mail, CU_TENSOR_MAP_DATA_TYPE_UINT32, 2, sc->mail, dims, strides, box, estr, CU_TENSOR_MAP_INTERLEAVE_NONE,
            CU_TENSOR_MAP_SWIZZLE_NONE, CU_TENSOR_MAP_L2_PROMOTION_NONE, CU_TENSOR_MAP_FLOAT_OOB_FILL_NONE);
    }
    make_map(enc, &tm_wm, d_in[4], 272, 128);
    make_map(enc, &tm_wu, d_in[5], 256, 256);
    if (fused) {
        mpnn_kernel<3><<<NCTA, THREADS, SM_ALLOC, cudaStreamPerThread>>>(x, e_attr, src, dst, w_msg, out, sc, tm_wm, tm_wu, tm_mail, tm_p);
    } else {
        mpnn_kernel<1><<<NCTA, THREADS, SM_ALLOC, cudaStreamPerThread>>>(x, e_attr, src, dst, w_msg, out, sc, tm_wm, tm_wu, tm_mail, tm_p);
        mpnn_kernel<2><<<NCTA, THREADS, SM_ALLOC, cudaStreamPerThread>>>(x, e_attr, src, dst, w_msg, out, sc, tm_wm, tm_wu, tm_mail, tm_p);
    }
}
```

```cpp
#include <cuda_runtime.h>
#include <cuda.h>
#include <cuda_bf16.h>
#include <stdint.h>
#include <stddef.h>

#define ROTATE 1
#define WU2AT 3
#define WU2LOAD { \
    asm volatile("mbarrier.arrive.expect_tx.shared.b64 _, [%0], %1;" ::"r"(mb + 16), "n"(32768) : "memory"); \
    tma2d(sb + SM_WU + 16384, &tm_wu, 0, 128, mb + 16); \
    tma2d(sb + SM_WU + 32768 + 16384, &tm_wu, 64, 128, mb + 16); }
#define XDELAY 1
#define QREG 4
#define ACQ 1
#define PUBAT 1
#define PFAT 2
#define W3REG 0

namespace {

constexpr int NN = 10000;
constexpr int EE = 160000;
constexpr int NCTA = 132;
constexpr int NPC = 76;
constexpr int NWR = 125;
constexpr int EPC = 1280;
constexpr int THREADS = 512;
constexpr int MCAP = 31;
constexpr int SCHUNK = NCTA * 8;
constexpr int RCHUNK = 128 * 8;
constexpr int CAP = 2048;
constexpr int NSPILL = NWR * MCAP - CAP;
#define PF1 0

static_assert(NCTA * NPC >= NN, "nodes");
static_assert(NWR * EPC == EE, "edges");
static_assert(NN <= 16384 && EPC < 2047 && NPC < 80, "entry packing");

constexpr int SLOT = 5120;
constexpr int SM_RING = 0;
constexpr int SM_W12 = 0;
constexpr int SM_WOFF = 65536;
constexpr int SM_OUT = 0;
constexpr int SM_EXT = 0;
constexpr int SM_AGG = 16 * SLOT;
constexpr int SM_WU = SM_AGG + 20480;
constexpr int SM_X = SM_WU + 65536;
constexpr int SM_ZL = SM_X + 8192;
constexpr int SM_Q = SM_X + 20480;
constexpr int SM_LIST = SM_Q + 20480;
constexpr int LISTB = (CAP + 64) * 4;
constexpr int SM_EID = SM_LIST + LISTB;
constexpr int SM_W3F = SM_EID + LISTB;
constexpr int SM_MISC = SM_W3F + 4096;
constexpr int SM_TRASH = SM_MISC + 2048;
constexpr int SM_TOTAL = SM_TRASH + 256;
constexpr int SM_ALLOC = SM_TOTAL;
static_assert(2 * LISTB >= SCHUNK * 16, "staging");
static_assert(SM_ALLOC <= 232448, "smem");

struct Misc {
    int cnt[NCTA];
    int ncnt[128];
    int off[100];
    int ovf;
    int anyovf;
    int total;
    int pad;
    int wovf[128];
    uint4 trash;
    unsigned long long mbar[3];
};
constexpr int MISC_ZERO16 = 124;
static_assert(offsetof(Misc, mbar) == MISC_ZERO16 * 16, "misc layout");
static_assert(sizeof(Misc) <= 2048, "misc");

struct Scratch {
    uint4 P[NN * 16];
    uint4 mail[NCTA * RCHUNK];
    uint2 ovf[NWR * EPC];
    uint2 spill[NCTA * NSPILL];
    unsigned sync[64];
};
__device__ Scratch g_sc;

#define TSTAMP(i) do {} while (0)

__device__ __forceinline__ uint32_t smem_u32(const void* p) { return (uint32_t)__cvta_generic_to_shared(p); }

template <int ROWS>
__device__ __forceinline__ uint32_t sw(int row, int chunk) {
    return (uint32_t)((chunk >> 3) * (ROWS * 128) + row * 128 + (((chunk & 7) ^ (row & 7)) << 4));
}

__device__ __forceinline__ constexpr int r_off(int j) {
    return j < 4 ? SM_WU + j * 4096 : j < 8 ? SM_WU + 32768 + (j - 4) * 4096 : SM_X + (j - 8) * 4096;
}
__device__ __forceinline__ void cp16(uint32_t dst, const void* src) {
    asm volatile("cp.async.cg.shared.global [%0], [%1], 16;" ::"r"(dst), "l"(src) : "memory");
}
__device__ __forceinline__ void cp16z(uint32_t dst, const void* src, int bytes) {
    asm volatile("cp.async.cg.shared.global [%0], [%1], 16, %2;" ::"r"(dst), "l"(src), "r"(bytes) : "memory");
}
__device__ __forceinline__ void cp16i(uint32_t dst, const void* src, int skip) {
    asm volatile("{.reg .pred p; setp.eq.s32 p, %2, 0; @p cp.async.cg.shared.global [%0], [%1], 16;}" ::"r"(dst), "l"(src), "r"(skip) : "memory");
}
__device__ __forceinline__ void cp_commit() { asm volatile("cp.async.commit_group;" ::: "memory"); }
template <int N>
__device__ __forceinline__ void cp_wait() { asm volatile("cp.async.wait_group %0;" ::"n"(N) : "memory"); }
template <int ID, int N>
__device__ __forceinline__ void bar_sync() { asm volatile("bar.sync %0, %1;" ::"n"(ID), "n"(N) : "memory"); }
template <int ID, int N>
__device__ __forceinline__ void bar_arrive() { asm volatile("bar.arrive %0, %1;" ::"n"(ID), "n"(N) : "memory"); }
__device__ __forceinline__ void fence_async() { asm volatile("fence.proxy.async.shared::cta;" ::: "memory"); }

__device__ __forceinline__ void ldsm4t(uint32_t (&r)[4], uint32_t a) {
    asm volatile("ldmatrix.sync.aligned.m8n8.x4.trans.shared.b16 {%0,%1,%2,%3}, [%4];"
                 : "=r"(r[0]), "=r"(r[1]), "=r"(r[2]), "=r"(r[3]) : "r"(a));
}
__device__ __forceinline__ uint4 lds128(uint32_t a) {
    uint4 v;
    asm volatile("ld.shared.v4.u32 {%0,%1,%2,%3}, [%4];" : "=r"(v.x), "=r"(v.y), "=r"(v.z), "=r"(v.w) : "r"(a));
    return v;
}
__device__ __forceinline__ uint2 lds64(uint32_t a) {
    uint2 v;
    asm volatile("ld.shared.v2.u32 {%0,%1}, [%2];" : "=r"(v.x), "=r"(v.y) : "r"(a));
    return v;
}
__device__ __forceinline__ uint32_t lds32(uint32_t a) {
    uint32_t v;
    asm volatile("ld.shared.u32 %0, [%1];" : "=r"(v) : "r"(a));
    return v;
}
__device__ __forceinline__ uint32_t lds16(uint32_t a) {
    uint32_t v;
    asm volatile("ld.shared.u16 %0, [%1];" : "=r"(v) : "r"(a));
    return v;
}
__device__ __forceinline__ void sts32(uint32_t a, uint32_t v) {
    asm volatile("st.shared.u32 [%0], %1;" ::"r"(a), "r"(v) : "memory");
}
__device__ __forceinline__ void stsm4t(uint32_t a, uint32_t r0, uint32_t r1, uint32_t r2, uint32_t r3) {
    asm volatile("stmatrix.sync.aligned.m8n8.x4.trans.shared.b16 [%0], {%1,%2,%3,%4};"
                 ::"r"(a), "r"(r0), "r"(r1), "r"(r2), "r"(r3) : "memory");
}
__device__ __forceinline__ void mma16(float (&d)[4], const uint32_t a0, const uint32_t a1, const uint32_t a2,
                                      const uint32_t a3, const uint32_t b0, const uint32_t b1) {
    asm("mma.sync.aligned.m16n8k16.row.col.f32.bf16.bf16.f32 {%0,%1,%2,%3}, {%4,%5,%6,%7}, {%8,%9}, {%0,%1,%2,%3};"
        : "+f"(d[0]), "+f"(d[1]), "+f"(d[2]), "+f"(d[3])
        : "r"(a0), "r"(a1), "r"(a2), "r"(a3), "r"(b0), "r"(b1));
}
__device__ __forceinline__ void mma8(float (&d)[4], const uint32_t a0, const uint32_t a1, const uint32_t b0) {
    asm("mma.sync.aligned.m16n8k8.row.col.f32.bf16.bf16.f32 {%0,%1,%2,%3}, {%4,%5}, {%6}, {%0,%1,%2,%3};"
        : "+f"(d[0]), "+f"(d[1]), "+f"(d[2]), "+f"(d[3])
        : "r"(a0), "r"(a1), "r"(b0));
}
__device__ __forceinline__ uint32_t movm(uint32_t a) {
    uint32_t d;
    asm("movmatrix.sync.aligned.m8n8.trans.b16 %0, %1;" : "=r"(d) : "r"(a));
    return d;
}
__device__ __forceinline__ void ldsm4tf(float (&r)[4], uint32_t a) {
    asm volatile("ldmatrix.sync.aligned.m8n8.x4.trans.shared.b16 {%0,%1,%2,%3}, [%4];"
                 : "=f"(r[0]), "=f"(r[1]), "=f"(r[2]), "=f"(r[3]) : "r"(a));
}
__device__ __forceinline__ int range_start(int r, int T) {
    const int t0 = ((r >> 2) * T) >> 2, n = ((((r >> 2) + 1) * T) >> 2) - t0, b = r & 3;
    return t0 + b * (n >> 2) + min(b, n & 3);
}
__device__ __forceinline__ uint32_t pack2(float lo, float hi) {
    uint32_t r;
    asm("cvt.rn.bf16x2.f32 %0, %1, %2;" : "=r"(r) : "f"(hi), "f"(lo));
    return r;
}
__device__ __forceinline__ uint32_t add2(uint32_t a, uint32_t b) {
    uint32_t r;
    asm("add.rn.bf16x2 %0, %1, %2;" : "=r"(r) : "r"(a), "r"(b));
    return r;
}
__device__ __forceinline__ float tanh_fast(float x) {
    float t;
    asm("tanh.approx.f32 %0, %1;" : "=f"(t) : "f"(x));
    return t;
}
__device__ __forceinline__ float silu_h(float h) { return fmaf(h, tanh_fast(h), h); }

__device__ __forceinline__ uint4 ld_relaxed128(const void* p) {
    uint4 v;
    asm volatile("ld.relaxed.gpu.global.v4.u32 {%0,%1,%2,%3}, [%4];" : "=r"(v.x), "=r"(v.y), "=r"(v.z), "=r"(v.w) : "l"(p) : "memory");
    return v;
}
__device__ __forceinline__ unsigned ld_relaxed32(const void* p) {
    unsigned v;
    asm volatile("ld.relaxed.gpu.global.u32 %0, [%1];" : "=r"(v) : "l"(p) : "memory");
    return v;
}
__device__ __forceinline__ unsigned ld_poll32(const void* p) {
    unsigned v;
    asm volatile("ld.acquire.gpu.global.u32 %0, [%1];" : "=r"(v) : "l"(p) : "memory");
    return v;
}
__device__ __forceinline__ void st_relaxed128(void* p, uint4 v) {
    asm volatile("st.relaxed.gpu.global.v4.u32 [%0], {%1,%2,%3,%4};" ::"l"(p), "r"(v.x), "r"(v.y), "r"(v.z), "r"(v.w) : "memory");
}
__device__ __forceinline__ uint32_t atoms_inc(uint32_t addr) {
    uint32_t r;
    asm volatile("atom.shared.add.u32 %0, [%1], 1;" : "=r"(r) : "r"(addr) : "memory");
    return r;
}
__device__ __forceinline__ void tma2d(uint32_t dst, const CUtensorMap* tm, int c0, int c1, uint32_t bar) {
    asm volatile("cp.async.bulk.tensor.2d.shared::cluster.global.mbarrier::complete_tx::bytes [%0], [%1, {%3, %4}], [%2];"
                 ::"r"(dst), "l"(tm), "r"(bar), "r"(c0), "r"(c1) : "memory");
}
__device__ __forceinline__ void mbar_wait(uint32_t bar) {
    uint32_t ok;
    int sp = 0;
    do {
        asm volatile("{.reg .pred p; mbarrier.try_wait.parity.shared.b64 p, [%1], 0; selp.u32 %0, 1, 0, p;}" : "=r"(ok) : "r"(bar) : "memory");
    } while (!ok && ++sp < (1 << 22));
}
template <int N>
__device__ __forceinline__ void cp_rows(uint32_t dst, const void* src) {
#pragma unroll
    for (int i = 0; i < N; i++)
        asm volatile("cp.async.cg.shared.global [%0], [%1], 16;" ::"r"(dst + i * 2048), "l"((const char*)src + i * 4096) : "memory");
}

#define ACC40(d)                                                                                              \
    "+f"(d[0]), "+f"(d[1]), "+f"(d[2]), "+f"(d[3]), "+f"(d[4]), "+f"(d[5]), "+f"(d[6]), "+f"(d[7]),         \
    "+f"(d[8]), "+f"(d[9]), "+f"(d[10]), "+f"(d[11]), "+f"(d[12]), "+f"(d[13]), "+f"(d[14]), "+f"(d[15]),   \
    "+f"(d[16]), "+f"(d[17]), "+f"(d[18]), "+f"(d[19]), "+f"(d[20]), "+f"(d[21]), "+f"(d[22]), "+f"(d[23]), \
    "+f"(d[24]), "+f"(d[25]), "+f"(d[26]), "+f"(d[27]), "+f"(d[28]), "+f"(d[29]), "+f"(d[30]), "+f"(d[31]), \
    "+f"(d[32]), "+f"(d[33]), "+f"(d[34]), "+f"(d[35]), "+f"(d[36]), "+f"(d[37]), "+f"(d[38]), "+f"(d[39])

template <int ACCUM>
__device__ __forceinline__ void wgmma_issue(float (&d)[40], uint32_t w_addr, uint32_t t_addr) {
    const uint32_t la = (w_addr >> 4) | 0x10000u, lb = (t_addr >> 4) | 0x10000u;
    asm volatile("wgmma.fence.sync.aligned;" ::: "memory");
#pragma unroll
    for (int ks = 0; ks < 8; ks++) {
        asm volatile(
            "{.reg .b64 da, db; .reg .pred p;\n"
            "setp.ne.s32 p, %43, 0;\n"
            "mov.b64 da, {%40, %42};\n"
            "mov.b64 db, {%41, %42};\n"
            "wgmma.mma_async.sync.aligned.m64n80k16.f32.bf16.bf16 "
            "{%0,%1,%2,%3,%4,%5,%6,%7,%8,%9,%10,%11,%12,%13,%14,%15,%16,%17,%18,%19,"
            "%20,%21,%22,%23,%24,%25,%26,%27,%28,%29,%30,%31,%32,%33,%34,%35,%36,%37,%38,%39},"
            "da, db, p, 1, 1, 1, 0;}"
            : ACC40(d)
            : "r"(la + ks * 128), "r"(lb + (ks >> 2) * 640 + (ks & 3) * 2), "r"(0x40000040u), "r"((ks > 0 || ACCUM) ? 1 : 0));
    }
    asm volatile("wgmma.commit_group.sync.aligned;" ::: "memory");
}
#define ACC8(d, b) "+f"(d[b]), "+f"(d[b + 1]), "+f"(d[b + 2]), "+f"(d[b + 3]), "+f"(d[b + 4]), "+f"(d[b + 5]), "+f"(d[b + 6]), "+f"(d[b + 7])
__device__ __forceinline__ void wgmma_issue_split(float (&d)[40], uint32_t w_addr, uint32_t t_addr) {
    const uint32_t la = (w_addr >> 4) | 0x10000u, lb = (t_addr >> 4) | 0x10000u;
    asm volatile("wgmma.fence.sync.aligned;" ::: "memory");
#pragma unroll
    for (int ks = 0; ks < 8; ks++)
        asm volatile(
            "{.reg .b64 da, db;\n"
            "mov.b64 da, {%24, %26};\n"
            "mov.b64 db, {%25, %26};\n"
            "wgmma.mma_async.sync.aligned.m64n48k16.f32.bf16.bf16 "
            "{%0,%1,%2,%3,%4,%5,%6,%7,%8,%9,%10,%11,%12,%13,%14,%15,%16,%17,%18,%19,%20,%21,%22,%23},"
            "da, db, 1, 1, 1, 1, 0;}"
            : ACC8(d, 0), ACC8(d, 8), ACC8(d, 16)
            : "r"(la + ks * 128), "r"(lb + (ks >> 2) * 640 + (ks & 3) * 2), "r"(0x40000040u));
    asm volatile("wgmma.commit_group.sync.aligned;" ::: "memory");
#pragma unroll
    for (int ks = 0; ks < 8; ks++)
        asm volatile(
            "{.reg .b64 da, db;\n"
            "mov.b64 da, {%16, %18};\n"
            "mov.b64 db, {%17, %18};\n"
            "wgmma.mma_async.sync.aligned.m64n32k16.f32.bf16.bf16 "
            "{%0,%1,%2,%3,%4,%5,%6,%7,%8,%9,%10,%11,%12,%13,%14,%15},"
            "da, db, 1, 1, 1, 1, 0;}"
            : ACC8(d, 24), ACC8(d, 32)
            : "r"(la + ks * 128), "r"(lb + 384 + (ks >> 2) * 640 + (ks & 3) * 2), "r"(0x40000040u));
    asm volatile("wgmma.commit_group.sync.aligned;" ::: "memory");
}
template <int N>
__device__ __forceinline__ void wgmma_wait(float (&d)[40]) {
    asm volatile("wgmma.wait_group.sync.aligned %40;" : ACC40(d) : "n"(N) : "memory");
}
__device__ __forceinline__ void store_tile_half(uint32_t a, const float (&d)[40]) {
#pragma unroll
    for (int j = 0; j < 10; j += 2)
        stsm4t(a + j * 1024, pack2(0.5f * d[4 * j], 0.5f * d[4 * j + 1]), pack2(0.5f * d[4 * j + 2], 0.5f * d[4 * j + 3]),
               pack2(0.5f * d[4 * j + 4], 0.5f * d[4 * j + 5]), pack2(0.5f * d[4 * j + 6], 0.5f * d[4 * j + 7]));
}

template <int MODE>
__global__ void __launch_bounds__(THREADS, 1)
mpnn_kernel(const __nv_bfloat16* __restrict__ x, const __nv_bfloat16* __restrict__ e_attr,
            const int* __restrict__ src, const int* __restrict__ dst,
            const __nv_bfloat16* __restrict__ w_msg,
            Scratch* __restrict__ sc,
            const __grid_constant__ CUtensorMap tm_wm, const __grid_constant__ CUtensorMap tm_wu,
            const __grid_constant__ CUtensorMap tm_mail, const __grid_constant__ CUtensorMap tm_p,
            const __grid_constant__ CUtensorMap tm_out, const __grid_constant__ CUtensorMap tm_out2) {
    extern __shared__ __align__(1024) uint8_t smem[];
    const uint32_t sb = smem_u32(smem);
    Misc* ms = reinterpret_cast<Misc*>(smem + SM_MISC);
    const unsigned tid = threadIdx.x, lane = tid & 31;
    __builtin_assume(tid < THREADS);
    const int warp = __shfl_sync(0xffffffffu, tid >> 5, 0);
    const unsigned cta = blockIdx.x;
    __builtin_assume(cta < NCTA);
    if (tid == 0) TSTAMP(0);

    const unsigned g = lane >> 2, q = lane & 3;
    const int node0 = cta * NPC;
    const uint32_t tile_a = sw<80>(((lane >> 4) & 1) * 8 + (lane & 7), (warp & 7) * 2 + ((lane >> 3) & 1));

    if (warp >= 8) {
        const unsigned tb = tid - 256;
        __builtin_assume(tb < 256);
        const bool writer = (MODE & 1) && cta < NWR;
        uint32_t dv[5], sv[5];
        if (writer) {
            const int* dp = dst + cta * EPC;
            const int* sp = src + cta * EPC;
            asm volatile("ld.global.nc.v4.u32 {%0,%1,%2,%3}, [%4];" : "=r"(dv[0]), "=r"(dv[1]), "=r"(dv[2]), "=r"(dv[3]) : "l"(dp + tb * 4));
            asm volatile("ld.global.nc.u32 %0, [%1];" : "=r"(dv[4]) : "l"(dp + 1024 + tb));
            asm volatile("ld.global.nc.v4.u32 {%0,%1,%2,%3}, [%4];" : "=r"(sv[0]), "=r"(sv[1]), "=r"(sv[2]), "=r"(sv[3]) : "l"(sp + tb * 4));
            asm volatile("ld.global.nc.u32 %0, [%1];" : "=r"(sv[4]) : "l"(sp + 1024 + tb));
        }
        bar_arrive<3, 512>();
        unsigned htarget = 0;
        if (tb == 0 && MODE == 3) htarget = ld_relaxed32(&sc->sync[32]);
        if (tb == 32) asm volatile("prefetch.tensormap [%0];" ::"l"(&tm_mail) : "memory");
        if (tb < MISC_ZERO16) reinterpret_cast<uint4*>(ms)[tb] = make_uint4(0, 0, 0, 0);
        bar_sync<2, 256>();
        if (tb == 0) TSTAMP(17);
        if (warp == 8) asm volatile("bar.arrive %0, 288;" ::"r"(5 + (writer ? dv[0] >> 30 : 0)) : "memory");
        if (writer) {
            uint32_t own[5], pos[5];
#pragma unroll
            for (int i = 0; i < 5; i++) {
                own[i] = (dv[i] * 55189u) >> 22;
                pos[i] = atoms_inc(sb + SM_MISC + own[i] * 4);
            }
            if (tb == 0) TSTAMP(18);
            uint32_t pmax = 0;
#pragma unroll
            for (int i = 0; i < 5; i++) {
                const uint32_t nl = dv[i] - own[i] * NPC;
                const uint32_t el1 = i < 4 ? tb * 4 + i + 1 : tb + 1025;
                sts32(sb + SM_LIST + own[i] * 128 + (pos[i] < MCAP ? pos[i] * 4 + 4 : 0), (sv[i] * 128u + nl) * 2048u + el1);
                pmax = max(pmax, pos[i]);
            }
            if (pmax >= MCAP) {
#pragma unroll
                for (int i = 0; i < 5; i++) {
                    if (pos[i] >= MCAP) {
                        const int k = atomicAdd(&ms->ovf, 1);
                        sc->ovf[cta * EPC + k] = make_uint2(dv[i], cta * EPC + (i < 4 ? tb * 4 + i : tb + 1024));
                    }
                }
                __threadfence();
            }
            if (tb == 0) TSTAMP(8);
            bar_sync<2, 256>();
            if (tb == 0) TSTAMP(19);
            if (tb < NCTA) sts32(sb + SM_LIST + tb * 128, ((uint32_t)ms->ovf << 11) | (uint32_t)ms->cnt[tb]);
            fence_async();
            bar_sync<2, 256>();
            if (tb == 0) {
                asm volatile("cp.async.bulk.tensor.2d.global.shared::cta.bulk_group [%0, {%2, %3}], [%1];"
                             ::"l"(&tm_mail), "r"(sb + SM_LIST), "r"(cta * 32), "r"(0) : "memory");
                asm volatile("cp.async.bulk.commit_group;" ::: "memory");
                TSTAMP(9);
                asm volatile("cp.async.bulk.wait_group 0;" ::: "memory");
                TSTAMP(23);
            }
        }
        if (!(MODE & 2)) return;
        if (MODE == 3) {
            if (tb == 0) {
                asm volatile("red.release.gpu.global.add.u32 [%0], 1;" ::"l"(&sc->sync[32]) : "memory");
                htarget = htarget - htarget % NCTA + NCTA;
                int sp = 0;
                while ((int)(ld_poll32(&sc->sync[32]) - htarget) < 0 && ++sp < (1 << 22)) {}
                TSTAMP(24);
            }
            bar_sync<2, 256>();
        }
        uint32_t w[2][8];
        {
            const uint4* mine = sc->mail + cta * RCHUNK + (tb >> 2) * 8 + (tb & 3);
            const uint4* mine2 = tb + 256 < NWR * 4 ? mine + 512 : mine;
            asm volatile("ld.relaxed.gpu.global.v4.u32 {%0,%1,%2,%3}, [%16];\n"
                         "ld.relaxed.gpu.global.v4.u32 {%8,%9,%10,%11}, [%17];\n"
                         "ld.relaxed.gpu.global.v4.u32 {%4,%5,%6,%7}, [%16+64];\n"
                         "ld.relaxed.gpu.global.v4.u32 {%12,%13,%14,%15}, [%17+64];"
                         : "=r"(w[0][0]), "=r"(w[0][1]), "=r"(w[0][2]), "=r"(w[0][3]), "=r"(w[0][4]), "=r"(w[0][5]), "=r"(w[0][6]), "=r"(w[0][7]),
                           "=r"(w[1][0]), "=r"(w[1][1]), "=r"(w[1][2]), "=r"(w[1][3]), "=r"(w[1][4]), "=r"(w[1][5]), "=r"(w[1][6]), "=r"(w[1][7])
                         : "l"(mine), "l"(mine2) : "memory");
        }
        uint32_t hd[2];
        hd[0] = __shfl_sync(0xffffffffu, w[0][0], lane & ~3u);
        hd[1] = __shfl_sync(0xffffffffu, w[1][0], lane & ~3u);
        if (tb + 256 >= NWR * 4) hd[1] = 0;
        if (tb == 0) TSTAMP(10);
        int lim[2];
#pragma unroll
        for (int b = 0; b < 2; b++) {
            if ((hd[b] & 0x7ffu) > MCAP) { ms->wovf[(tb >> 2) + 64 * b] = hd[b] >> 11; ms->anyovf = 1; }
            lim[b] = (int)(hd[b] & 0x7ffu) - (int)(tb & 3) * 4;
        }
        const bool second = __any_sync(0xffffffffu, max(lim[0], lim[1]) >= 16);
        const uint32_t dummy = (96u + lane) << 11;
        if ((tb & 3) == 0) w[0][0] = w[1][0] = dummy;
        uint32_t rk[2][8];
        const uint32_t nc = smem_u32(ms->ncnt);
        auto hist = [&](int i0) {
#pragma unroll
            for (int b = 0; b < 2; b++)
#pragma unroll
                for (int i = i0; i < i0 + 4; i++) {
                    w[b][i] = lim[b] >= (i & 3) + (i >> 2) * 16 ? w[b][i] : dummy;
                    rk[b][i] = atoms_inc(nc + ((w[b][i] >> 9) & 0x1fc));
                }
        };
        hist(0);
        if (second) hist(4);
        const uint32_t wo = sb + SM_WOFF + (warp - 8) * 512;
        sts32(wo + 384 + lane * 4, 1u << 20);
        if (tb == 0) TSTAMP(20);
        bar_sync<2, 256>();
        int total;
        {
            const int c0 = lds32(nc + lane * 12), c1 = lds32(nc + lane * 12 + 4), c2 = lds32(nc + lane * 12 + 8);
            int s = c0 + c1 + c2;
#pragma unroll
            for (int d = 1; d < 32; d <<= 1) {
                const int t = __shfl_up_sync(0xffffffffu, s, d);
                if (lane >= d) s += t;
            }
            sts32(wo + lane * 12, s - c2 - c1 - c0);
            sts32(wo + lane * 12 + 4, s - c2 - c1);
            sts32(wo + lane * 12 + 8, s - c2);
            total = __shfl_sync(0xffffffffu, s, 31);
            if (warp == 15) {
                ms->off[lane * 3] = min(s - c2 - c1 - c0, CAP);
                ms->off[lane * 3 + 1] = min(s - c2 - c1, CAP);
                ms->off[lane * 3 + 2] = min(s - c2, CAP);
                if (lane == 31) { ms->off[96] = min(s, CAP); ms->total = s; if (s > CAP) ms->anyovf = 1; }
                if (total < CAP) {
                    const uint32_t pa = sb + SM_LIST + (total + lane) * 4;
                    sts32(pa, (79u * 128u + 7u * 16u) << 16);
                    sts32(pa + LISTB, 0u);
                    if (lane < 16) sts32(pa + 128, (79u * 128u + 7u * 16u) << 16);
                }
            }
            __syncwarp();
        }
        if (tb == 0) TSTAMP(22);
        const uint32_t eb = (tb >> 2) * EPC - 1;
        auto scatter = [&](int i0) {
#pragma unroll
            for (int b = 0; b < 2; b++)
#pragma unroll
                for (int i = i0; i < i0 + 4; i++) rk[b][i] += lds32(wo + ((w[b][i] >> 9) & 0x1fc));
#pragma unroll
            for (int b = 0; b < 2; b++)
#pragma unroll
                for (int i = i0; i < i0 + 4; i++) {
                    const uint32_t a = sb + SM_LIST + min(rk[b][i], (uint32_t)(CAP + 63)) * 4;
                    sts32(a, (w[b][i] >> 18) | ((w[b][i] << 12) & 0x3f800000u) | ((w[b][i] << 9) & 0x700000u));
                    sts32(a + LISTB, eb + b * (64 * EPC) + (w[b][i] & 0x7ff));
                }
            if (total > CAP) {
#pragma unroll
                for (int b = 0; b < 2; b++)
#pragma unroll
                    for (int i = i0; i < i0 + 4; i++)
                        if (rk[b][i] >= CAP && rk[b][i] < (1u << 20))
                            sc->spill[cta * NSPILL + rk[b][i] - CAP] = make_uint2(node0 + ((w[b][i] >> 11) & 127), eb + b * (64 * EPC) + (w[b][i] & 0x7ff));
            }
        };
        scatter(0);
        if (second) scatter(4);
        if (tb == 0) TSTAMP(11);
    } else {
        unsigned target = 0;
        const uint32_t mb = smem_u32(ms->mbar);
        const char* epf = reinterpret_cast<const char*>(e_attr) + (size_t)cta * (EPC * 32);
        {
            const unsigned r0 = tid >> 4, c0 = tid & 15;
            bar_sync<3, 512>();
            cp_rows<8>(sb + SM_W12 + sw<256>(r0, c0), reinterpret_cast<const uint4*>(w_msg) + tid);
            const uint32_t dx = sb + SM_X + sw<80>(r0, c0);
            const uint4* xg = reinterpret_cast<const uint4*>(x) + c0;
        if (tid == 32) asm volatile("prefetch.tensormap [%0];" ::"l"(&tm_p) : "memory");
        if (tid == 64) asm volatile("prefetch.tensormap [%0];" ::"l"(&tm_wu) : "memory");
        if (tid == 96) asm volatile("prefetch.tensormap [%0];" ::"l"(&tm_out) : "memory");
        if (tid == 128) asm volatile("prefetch.tensormap [%0];" ::"l"(&tm_out2) : "memory");
        if (tid == 0) {
            if (MODE == 3) target = ld_relaxed32(&sc->sync[0]);
            asm volatile("mbarrier.init.shared.b64 [%0], 1;" ::"r"(mb) : "memory");
            asm volatile("mbarrier.init.shared.b64 [%0], 1;" ::"r"(mb + 8) : "memory");
            asm volatile("mbarrier.init.shared.b64 [%0], 1;" ::"r"(mb + 16) : "memory");
            asm volatile("fence.mbarrier_init.release.cluster;" ::: "memory");
            asm volatile("mbarrier.arrive.expect_tx.shared.b64 _, [%0], %1;" ::"r"(mb), "n"(32768) : "memory");
            tma2d(sb + SM_W12 + 16384, &tm_wm, 0, 128, mb);
            tma2d(sb + SM_W12 + 32768 + 16384, &tm_wm, 64, 128, mb);
            if (MODE & 2) {
                asm volatile("mbarrier.arrive.expect_tx.shared.b64 _, [%0], %1;" ::"r"(mb + 8), "n"(32768) : "memory");
                tma2d(sb + SM_WU, &tm_wu, 0, 0, mb + 8);
                tma2d(sb + SM_WU + 32768, &tm_wu, 64, 0, mb + 8);
                if (WU2AT == 0) WU2LOAD
            }
            if (PF1 > 0 && cta < NWR)
                asm volatile("cp.async.bulk.prefetch.L2.global [%0], %1;" ::"l"(epf), "n"(PF1 > 0 ? PF1 : 16) : "memory");
        }
            bar_sync<5, 288>();
#pragma unroll
            for (int i = 0; i < 5; i++) cp16(dx + i * 2048, xg + min(node0 + r0 + i * 16, (unsigned)(NN - 1)) * 16);
            cp_commit();
        }
        const int wg = warp >> 2;
        float a0[40];
        cp_wait<0>();
        fence_async();
        bar_sync<1, 256>();
        if (tid == 0) TSTAMP(1);
        wgmma_issue<0>(a0, sb + SM_W12 + wg * 32768, sb + SM_X);
        if (PFAT == 3 && tid == 128) {
            if (PF1 < EPC * 32 && cta < NWR)
                asm volatile("cp.async.bulk.prefetch.L2.global [%0], %1;" ::"l"(epf + PF1), "n"(PF1 < EPC * 32 ? EPC * 32 - PF1 : 16) : "memory");
        }
        unsigned short w3v[8];
        {
            const unsigned short* w3 = reinterpret_cast<const unsigned short*>(w_msg) + (256 + 4 * q) * 128 + warp * 16 + g;
#pragma unroll
            for (int i = 0; i < 4; i++) {
                asm volatile("ld.global.u16 %0, [%1];" : "=h"(w3v[i]) : "l"(w3 + i * 128) : "memory");
                asm volatile("ld.global.u16 %0, [%1];" : "=h"(w3v[4 + i]) : "l"(w3 + i * 128 + 8) : "memory");
            }
        }
        wgmma_wait<0>(a0);
        if (tid == 0) TSTAMP(15);
        store_tile_half(sb + SM_AGG + tile_a, a0);
        fence_async();
        bar_sync<1, 256>();
        if (tid == 0) TSTAMP(16);
        if (tid == 0) {
            if (MODE & 1) {
                asm volatile("cp.async.bulk.tensor.2d.global.shared::cta.bulk_group [%0, {%2, %3}], [%1];"
                             ::"l"(&tm_p), "r"(sb + SM_AGG), "r"(0), "r"(node0) : "memory");
                asm volatile("cp.async.bulk.tensor.2d.global.shared::cta.bulk_group [%0, {%2, %3}], [%1];"
                             ::"l"(&tm_p), "r"(sb + SM_AGG + 10240), "r"(64), "r"(node0) : "memory");
                asm volatile("cp.async.bulk.commit_group;" ::: "memory");
            }
            if ((MODE & 2) && WU2AT == 1) WU2LOAD
            if (PFAT == 0) {
            if (PF1 < EPC * 32 && cta < NWR)
                asm volatile("cp.async.bulk.prefetch.L2.global [%0], %1;" ::"l"(epf + PF1), "n"(PF1 < EPC * 32 ? EPC * 32 - PF1 : 16) : "memory");
            }
        }
        if (PFAT == 1 && tid == 128) {
            if (PF1 < EPC * 32 && cta < NWR)
                asm volatile("cp.async.bulk.prefetch.L2.global [%0], %1;" ::"l"(epf + PF1), "n"(PF1 < EPC * 32 ? EPC * 32 - PF1 : 16) : "memory");
        }
        mbar_wait(mb);
        if (!(MODE & 2)) {
            asm volatile("cp.async.bulk.wait_group 0;" ::: "memory");
            return;
        }
        float a1[40];
        wgmma_issue<0>(a0, sb + SM_W12 + wg * 32768 + 16384, sb + SM_X);
        mbar_wait(mb + 8);
        wgmma_issue<0>(a1, sb + SM_WU + wg * 32768, sb + SM_X);
        if (tid == 0 && MODE == 3) {
            TSTAMP(4);
            asm volatile("cp.async.bulk.wait_group 0;" ::: "memory");
            TSTAMP(2);
            asm volatile("red.release.gpu.global.add.u32 [%0], 1;" ::"l"(&sc->sync[0]) : "memory");
            TSTAMP(3);
            if (PFAT == 2) {
            if (PF1 < EPC * 32 && cta < NWR)
                asm volatile("cp.async.bulk.prefetch.L2.global [%0], %1;" ::"l"(epf + PF1), "n"(PF1 < EPC * 32 ? EPC * 32 - PF1 : 16) : "memory");
            }
        }
        wgmma_wait<1>(a0);
        if (tid == 0) TSTAMP(25);
        store_tile_half(sb + SM_Q + tile_a, a0);
        {
            const __nv_bfloat162 hf = __floats2bfloat162_rn(0.5f, 0.5f);
            uint32_t f[4] = {w3v[0] | ((uint32_t)w3v[1] << 16), w3v[4] | ((uint32_t)w3v[5] << 16),
                             w3v[2] | ((uint32_t)w3v[3] << 16), w3v[6] | ((uint32_t)w3v[7] << 16)};
#pragma unroll
            for (int i = 0; i < 4; i++) {
                __nv_bfloat162 h = __hmul2(*reinterpret_cast<__nv_bfloat162*>(&f[i]), hf);
                f[i] = *reinterpret_cast<uint32_t*>(&h);
            }
            reinterpret_cast<uint4*>(smem + SM_W3F)[tid] = make_uint4(f[0], f[1], f[2], f[3]);
        }
        wgmma_wait<0>(a1);
        bar_sync<1, 256>();
#pragma unroll
        for (int j = 0; j < 10; j++)
            *reinterpret_cast<float4*>(smem + r_off(j) + tid * 16) = make_float4(a1[4 * j], a1[4 * j + 1], a1[4 * j + 2], a1[4 * j + 3]);
        if (tid >= 224) *reinterpret_cast<uint4*>(smem + SM_ZL + (lane >> 3) * 1024 + (lane & 7) * 16) = make_uint4(0, 0, 0, 0);
        if (tid == 32 && WU2AT == 2) WU2LOAD
        if (tid == 0 && MODE == 3) {
            TSTAMP(7);
            target = target - target % NCTA + NCTA;
            int sp = 0;
            while ((int)(ld_poll32(&sc->sync[0]) - target) < 0 && ++sp < (1 << 22)) {}
            TSTAMP(5);
        }
    }
    bar_sync<0, 512>();
    if (tid == 0) TSTAMP(6);

    const int M = ms->off[96];
    const int T = (M + 15) >> 4;
    const int rg = (warp & 3) * 4 + (warp >> 2);
    const int s = range_start(rg, T) * 16;
    const int e = min(range_start(rg + 1, T) * 16, M);
    const uint32_t ring = sb + SM_RING + rg * SLOT;
    {
        const unsigned fr = lane >> 3, fc = lane & 7;
        const char* Pb0 = reinterpret_cast<const char*>(sc->P) + ((fc ^ fr) << 4);
        const char* Pb1 = reinterpret_cast<const char*>(sc->P) + ((fc ^ fr ^ 4) << 4);
        const char* Eb = reinterpret_cast<const char*>(e_attr) + (lane & 1) * 16;
        const uint32_t fdst = ring + lane * 16;
        const unsigned ledge = (lane & 6) | ((lane ^ (lane >> 3) ^ 1) & 1);
        const uint32_t lz = ((lane & 1) ? ring + ledge * 128 : sb + SM_ZL) + (((lane >> 4) ^ ledge) << 4);
        const uint32_t w3a = sb + SM_W3F + lane * 16;
        uint32_t sn[4], ei;
        auto fidx = [&](int tb) {
#pragma unroll
            for (int i = 0; i < 4; i++) sn[i] = lds16(sb + SM_LIST + (tb + fr) * 4 + i * 16);
            ei = lds32(sb + SM_EID + (tb + (lane >> 1)) * 4);
        };
        auto fetchP = [&](int h, int skip) {
#pragma unroll
            for (int i = 0; i < 4; i++) cp16i(fdst + h * 2048 + i * 512, ((i & 1) ? Pb1 : Pb0) + (size_t)sn[i] * 256 + h * 128, skip);
        };
        auto fetchE = [&](int skip) { cp16i(fdst + 4096, Eb + (size_t)ei * 32, skip); };
        uint4 w3r[W3REG > 0 ? W3REG : 1];
        int lo = s;
        auto first_fetch = [&]() {
            const int skip = lo >= e;
            fetchE(skip);
            fetchP(0, skip);
            cp_commit();
            fetchP(1, skip);
            cp_commit();
        };
        fidx(lo);
        if (warp >= 4) asm volatile("bar.sync %0, 256;" ::"r"(4 + (warp >> 2)) : "memory");
        first_fetch();
        if (warp < 12) asm volatile("bar.arrive %0, 256;" ::"r"(5 + (warp >> 2)) : "memory");
        if (tid == 480 && WU2AT == 3) { const uint32_t mb = smem_u32(ms->mbar); WU2LOAD }
        {
            const int nd = warp * 5 + min(lane, 4u);
            unsigned em = __ballot_sync(0xffffffffu, ms->off[nd] == ms->off[nd + 1]) & 31u;
            while (em) {
                const int k = __ffs(em) - 1;
                em &= em - 1;
                *reinterpret_cast<uint2*>(smem + SM_AGG + sw<80>(warp * 5 + k, lane >> 1) + (lane & 1) * 8) = make_uint2(0, 0);
            }
        }
            while (lo < e) {
            int tb = lo & ~15;
            const int nb = lds32(sb + SM_LIST + lo * 4) >> 23;
            const int hi = min(e, ms->off[min(nb + 8, 96)]);
            const int o0 = ms->off[nb + 2 * q];
            const uint32_t cn0 = ms->off[nb + 2 * q + 1] - o0;
            const uint32_t cn1 = ms->off[nb + 2 * q + 2] - o0 - cn0;
            uint32_t fa, fs;
            {
                const int nd = nb + (lane & 7);
                const int p0 = ms->off[nd], p1 = ms->off[nd + 1];
                const bool full = p0 >= s && p1 <= e && p1 > p0;
                const bool fst = p0 < s && p1 > s;
                const bool lst = p0 >= s && p0 < e && p1 > e;
                fa = full ? sb + SM_AGG + sw<80>(nd, lane >> 3)
                          : (fst ? ring + 4608 : lst ? ring + 4864 : sb + SM_TRASH) + (lane >> 3) * 16;
                fs = full ? 10240 : 128;
            }
#pragma unroll
            for (int m = 0; m < W3REG; m++) w3r[m] = lds128(w3a + m * 512);
            float acc[8][4];
#pragma unroll
            for (int m = 0; m < 8; m++)
#pragma unroll
                for (int k = 0; k < 4; k++) acc[m][k] = 0.f;
            uint32_t qf[4][4];
            const uint32_t qa = sb + SM_Q + sw<80>(min(nb + (int)(lane & 7), 79), lane >> 3);
#pragma unroll
            for (int j = 0; j < QREG; j++) ldsm4t(qf[j], (qa ^ ((j & 1) << 6)) + (j >> 1) * 10240);
            uint32_t q0, q1, ss0, ss1;
            uint2 e0, e1;
            int last;
            float c[2][2][2][4];
            auto top = [&]() {
                const uint32_t u = tb + g - o0;
                q0 = (u < cn0 ? 0x3F80u : 0u) | (u - cn0 < cn1 ? 0x3F800000u : 0u);
                q1 = (u + 8 < cn0 ? 0x3F80u : 0u) | (u + 8 - cn0 < cn1 ? 0x3F800000u : 0u);
                tb += 16;
                fidx(tb);
                cp_wait<1>();
                __syncwarp();
                e0 = lds64(ring + 4096 + lane * 8);
                e1 = lds64(ring + 4096 + 256 + lane * 8);
            };
            auto stageA = [&](int j, float (&cc)[2][2][4]) {
                if (j == 2) { cp_wait<1>(); __syncwarp(); }
                if (j >= QREG) ldsm4t(qf[j], (qa ^ ((j & 1) << 6)) + (j >> 1) * 10240);
#pragma unroll
                for (int mm = 0; mm < 2; mm++) {
                    const int m = 2 * j + mm;
                    const uint4 wf = m < W3REG ? w3r[m < W3REG ? m : 0] : lds128(w3a + m * 512);
                    ldsm4tf(cc[mm][0], (lz ^ ((m & 3) << 5)) + (m >> 2) * 2048);
                    ldsm4tf(cc[mm][1], (lz ^ ((m & 3) << 5)) + (m >> 2) * 2048 + 1024);
                    mma8(cc[mm][0], qf[j][2 * mm], qf[j][2 * mm + 1], q0);
                    mma8(cc[mm][1], qf[j][2 * mm], qf[j][2 * mm + 1], q1);
                    mma16(cc[mm][0], wf.x, wf.y, wf.z, wf.w, e0.x, e0.y);
                    mma16(cc[mm][1], wf.x, wf.y, wf.z, wf.w, e1.x, e1.y);
                }
                if (j & 1) {
                    __syncwarp();
                    if (j == 1) fetchE(last);
                    fetchP(j >> 1, last);
                    cp_commit();
                }
            };
            auto stageB = [&](int j, float (&cc)[2][2][4]) {
#pragma unroll
                for (int mm = 0; mm < 2; mm++) {
                    const uint32_t a0 = pack2(silu_h(cc[mm][0][0]), silu_h(cc[mm][0][1]));
                    const uint32_t a1 = pack2(silu_h(cc[mm][0][2]), silu_h(cc[mm][0][3]));
                    const uint32_t a2 = pack2(silu_h(cc[mm][1][0]), silu_h(cc[mm][1][1]));
                    const uint32_t a3 = pack2(silu_h(cc[mm][1][2]), silu_h(cc[mm][1][3]));
                    mma16(acc[2 * j + mm], a0, a1, a2, a3, ss0, ss1);
                }
            };
            top();
            stageA(0, c[0]);
#pragma unroll 1
            for (;;) {
                ss0 = movm(q0);
                ss1 = movm(q1);
                last = tb >= hi;
                stageA(1, c[1]); stageB(0, c[0]);
                stageA(2, c[0]); stageB(1, c[1]);
                stageA(3, c[1]); stageB(2, c[0]);
                top();
                stageA(0, c[0]);
                stageB(3, c[1]);
                if (last) break;
            }
#pragma unroll
            for (int j = 0; j < 4; j++)
                stsm4t((fa ^ ((j & 1) << 6)) + (j >> 1) * fs, pack2(acc[2 * j][0], acc[2 * j][1]), pack2(acc[2 * j][2], acc[2 * j][3]),
                       pack2(acc[2 * j + 1][0], acc[2 * j + 1][1]), pack2(acc[2 * j + 1][2], acc[2 * j + 1][3]));
            lo = hi;
            if (lo < e) {
                cp_wait<0>();
                __syncwarp();
                fidx(lo & ~15);
                first_fetch();
            }
        }
    }
    if (warp >= 8) {
        const int tb = tid - 256;
        const int r1 = (warp - 8) * 2 + (lane >> 4);
        const unsigned hl = lane & 15;
        const int s1 = range_start(r1, T) * 16;
        const int e1 = min(range_start(r1 + 1, T) * 16, M);
        const int nl = lds32(sb + SM_LIST + max(e1 - 1, 0) * 4) >> 23;
        const int o1 = ms->off[nl + 1];
        const bool fx = s1 < e1 && ms->off[nl] >= s1 && o1 > e1;
        const bool slow = ms->anyovf;
        bar_sync<0, 512>();
        if (tb == 0) TSTAMP(21);
        if (fx) {
            uint4 u = lds128(sb + SM_RING + r1 * SLOT + 4864 + hl * 16);
            float v[8];
            v[0] = __uint_as_float(u.x << 16); v[1] = __uint_as_float(u.x & 0xffff0000u);
            v[2] = __uint_as_float(u.y << 16); v[3] = __uint_as_float(u.y & 0xffff0000u);
            v[4] = __uint_as_float(u.z << 16); v[5] = __uint_as_float(u.z & 0xffff0000u);
            v[6] = __uint_as_float(u.w << 16); v[7] = __uint_as_float(u.w & 0xffff0000u);
            int s2 = e1;
            for (int r2 = r1 + 1; s2 < o1; r2++) {
                const int e2 = range_start(r2 + 1, T) * 16;
                if (s2 < e2) {
                    u = lds128(sb + SM_RING + r2 * SLOT + 4608 + hl * 16);
                    v[0] += __uint_as_float(u.x << 16); v[1] += __uint_as_float(u.x & 0xffff0000u);
                    v[2] += __uint_as_float(u.y << 16); v[3] += __uint_as_float(u.y & 0xffff0000u);
                    v[4] += __uint_as_float(u.z << 16); v[5] += __uint_as_float(u.z & 0xffff0000u);
                    v[6] += __uint_as_float(u.w << 16); v[7] += __uint_as_float(u.w & 0xffff0000u);
                }
                s2 = e2;
            }
            *reinterpret_cast<uint4*>(smem + SM_AGG + sw<80>(nl, hl)) =
                make_uint4(pack2(v[0], v[1]), pack2(v[2], v[3]), pack2(v[4], v[5]), pack2(v[6], v[7]));
        }
        if (slow) {
            __threadfence();
            bar_sync<2, 256>();
            float* ext = reinterpret_cast<float*>(smem + SM_EXT);
            for (int i = tb; i < 80 * 128; i += 256) ext[i] = 0.f;
            bar_sync<2, 256>();
            const char* Pb = reinterpret_cast<const char*>(sc->P);
            for (int w = -1; w < NWR; w++) {
                const int cnt = w < 0 ? ms->total - CAP : ms->wovf[w];
                for (int k = warp - 8; k < cnt; k += 8) {
                    uint2 en;
                    const uint2* ep = w < 0 ? sc->spill + cta * NSPILL + k : sc->ovf + w * EPC + k;
                    asm volatile("ld.relaxed.gpu.global.v2.u32 {%0,%1}, [%2];" : "=r"(en.x), "=r"(en.y) : "l"(ep) : "memory");
                    const int nl = (int)en.x - node0;
                    const uint32_t eid = en.y;
                    if (nl < 0 || nl >= NPC) continue;
                    const uint32_t sn = src[eid];
                    for (int u = 0; u < 4; u++) {
                        const int f = lane * 4 + u;
                        float h = 0.f;
                        for (int kk = 0; kk < 16; kk++)
                            h = fmaf(__bfloat162float(e_attr[(size_t)eid * 16 + kk]), __bfloat162float(w_msg[(256 + kk) * 128 + f]), h);
                        h = 0.5f * h + __bfloat162float(*reinterpret_cast<const __nv_bfloat16*>(Pb + sn * 256 + f * 2)) +
                            __bfloat162float(*reinterpret_cast<const __nv_bfloat16*>(smem + SM_Q + sw<80>(nl, f >> 3) + (f & 7) * 2));
                        atomicAdd(&ext[nl * 128 + f], __bfloat162float(__float2bfloat16_rn(silu_h(h))));
                    }
                }
            }
            bar_sync<2, 256>();
            for (int i = tb; i < 80 * 128; i += 256) {
                const int r = i >> 7, f = i & 127;
                __nv_bfloat16* pp = reinterpret_cast<__nv_bfloat16*>(smem + SM_AGG + sw<80>(r, f >> 3) + (f & 7) * 2);
                *pp = __float2bfloat16_rn(__bfloat162float(*pp) + ext[i]);
            }
        }
        fence_async();
        bar_arrive<4, 512>();
        return;
    }
    {
        const int wg = warp >> 2;
        float a0[40];
        bar_arrive<0, 512>();
        fence_async();
#pragma unroll
        for (int j = 0; j < 10; j++) {
            const float4 v = *reinterpret_cast<const float4*>(smem + r_off(j) + tid * 16);
            a0[4 * j] = v.x; a0[4 * j + 1] = v.y; a0[4 * j + 2] = v.z; a0[4 * j + 3] = v.w;
        }
        mbar_wait(smem_u32(ms->mbar) + 16);
        bar_sync<4, 512>();
        if (tid == 0) TSTAMP(14);
        asm volatile("" : ACC40(a0)::"memory");
        wgmma_issue_split(a0, sb + SM_WU + wg * 32768 + 16384, sb + SM_AGG);
        auto emit = [&](int j0, int j1, const CUtensorMap* tm) {
#pragma unroll
            for (int j = j0; j < j1; j += 2) {
                uint32_t r[4];
#pragma unroll
                for (int k = 0; k < 4; k++) r[k] = pack2(silu_h(0.5f * a0[4 * j + 2 * k]), silu_h(0.5f * a0[4 * j + 2 * k + 1]));
                stsm4t(sb + SM_OUT + tile_a + j * 1024, r[0], r[1], r[2], r[3]);
            }
            fence_async();
            if (wg == 0) bar_sync<1, 128>(); else bar_sync<3, 128>();
            if ((tid & 127) == 0) {
                asm volatile("cp.async.bulk.tensor.2d.global.shared::cta.bulk_group [%0, {%2, %3}], [%1];"
                             ::"l"(tm), "r"(sb + SM_OUT + wg * 10240 + j0 * 1024), "r"(wg * 64), "r"(node0 + j0 * 8) : "memory");
                asm volatile("cp.async.bulk.commit_group;" ::: "memory");
            }
        };
        asm volatile("wgmma.wait_group.sync.aligned 1;" : ACC8(a0, 0), ACC8(a0, 8), ACC8(a0, 16)::"memory");
        if (tid == 0) TSTAMP(26);
        emit(0, 6, &tm_out);
        asm volatile("wgmma.wait_group.sync.aligned 0;" : ACC8(a0, 24), ACC8(a0, 32)::"memory");
        emit(6, 10, &tm_out2);
        if ((tid & 127) == 0) asm volatile("cp.async.bulk.wait_group.read 0;" ::: "memory");
    }
    if (tid == 0) TSTAMP(12);
}

}

typedef CUresult (*EncodeFn)(CUtensorMap*, CUtensorMapDataType, cuuint32_t, void*, const cuuint64_t*, const cuuint64_t*,
                             const cuuint32_t*, const cuuint32_t*, CUtensorMapInterleave, CUtensorMapSwizzle,
                             CUtensorMapL2promotion, CUtensorMapFloatOOBfill);

static void make_map(EncodeFn enc, CUtensorMap* tm, const void* base, int rows, int box_rows) {
    const cuuint64_t dims[2] = {128, (cuuint64_t)rows};
    const cuuint64_t strides[1] = {256};
    const cuuint32_t box[2] = {64, (cuuint32_t)box_rows};
    const cuuint32_t estr[2] = {1, 1};
    enc(tm, CU_TENSOR_MAP_DATA_TYPE_BFLOAT16, 2, const_cast<void*>(base), dims, strides, box, estr, CU_TENSOR_MAP_INTERLEAVE_NONE,
        CU_TENSOR_MAP_SWIZZLE_128B, CU_TENSOR_MAP_L2_PROMOTION_NONE, CU_TENSOR_MAP_FLOAT_OOB_FILL_NONE);
}

extern "C" void kernel_launch(void* const* d_in, const int* in_sizes, int n_in, void* d_out, int out_size) {
    const __nv_bfloat16* x = (const __nv_bfloat16*)d_in[0];
    const __nv_bfloat16* e_attr = (const __nv_bfloat16*)d_in[1];
    const int* src = (const int*)d_in[2];
    const int* dst = (const int*)d_in[3];
    const __nv_bfloat16* w_msg = (const __nv_bfloat16*)d_in[4];

    static int fused = -1;
    static Scratch* sc = nullptr;
    static EncodeFn enc = nullptr;
    if (fused < 0) {
        cudaFuncSetAttribute(mpnn_kernel<1>, cudaFuncAttributeMaxDynamicSharedMemorySize, SM_ALLOC);
        cudaFuncSetAttribute(mpnn_kernel<2>, cudaFuncAttributeMaxDynamicSharedMemorySize, SM_ALLOC);
        cudaFuncSetAttribute(mpnn_kernel<3>, cudaFuncAttributeMaxDynamicSharedMemorySize, SM_ALLOC);
        int dev = 0, sms = 0, occ = 0;
        cudaGetDevice(&dev);
        cudaDeviceGetAttribute(&sms, cudaDevAttrMultiProcessorCount, dev);
        cudaOccupancyMaxActiveBlocksPerMultiprocessor(&occ, mpnn_kernel<3>, THREADS, SM_ALLOC);
        cudaGetSymbolAddress((void**)&sc, g_sc);
        cudaDriverEntryPointQueryResult qr;
        cudaGetDriverEntryPoint("cuTensorMapEncodeTiled", (void**)&enc, cudaEnableDefault, &qr);
        fused = (sms * occ >= NCTA) ? 1 : 0;
    }
    CUtensorMap tm_wm, tm_wu, tm_mail, tm_p, tm_out, tm_out2;
    make_map(enc, &tm_out, d_out, NN, 48);
    make_map(enc, &tm_out2, d_out, NN, NPC - 48);
    make_map(enc, &tm_p, sc->P, NN, NPC);
    {
        const cuuint64_t dims[2] = {RCHUNK * 4, NCTA};
        const cuuint64_t strides[1] = {RCHUNK * 16};
        const cuuint32_t box[2] = {32, NCTA};
        const cuuint32_t estr[2] = {1, 1};
        enc(&tm_mail, CU_TENSOR_MAP_DATA_TYPE_UINT32, 2, sc->mail, dims, strides, box, estr, CU_TENSOR_MAP_INTERLEAVE_NONE,
            CU_TENSOR_MAP_SWIZZLE_NONE, CU_TENSOR_MAP_L2_PROMOTION_NONE, CU_TENSOR_MAP_FLOAT_OOB_FILL_NONE);
    }
    make_map(enc, &tm_wm, d_in[4], 272, 128);
    make_map(enc, &tm_wu, d_in[5], 256, 128);
    if (fused) {
        mpnn_kernel<3><<<NCTA, THREADS, SM_ALLOC, cudaStreamPerThread>>>(x, e_attr, src, dst, w_msg, sc, tm_wm, tm_wu, tm_mail, tm_p, tm_out, tm_out2);
    } else {
        mpnn_kernel<1><<<NCTA, THREADS, SM_ALLOC, cudaStreamPerThread>>>(x, e_attr, src, dst, w_msg, sc, tm_wm, tm_wu, tm_mail, tm_p, tm_out, tm_out2);
        mpnn_kernel<2><<<NCTA, THREADS, SM_ALLOC, cudaStreamPerThread>>>(x, e_attr, src, dst, w_msg, sc, tm_wm, tm_wu, tm_mail, tm_p, tm_out, tm_out2);
    }
}
```

```cpp
#include <cuda_runtime.h>
#include <cuda.h>
#include <cuda_bf16.h>
#include <stdint.h>
#include <stddef.h>

namespace {

constexpr int NN = 10000;
constexpr int EE = 160000;
constexpr int NCTA = 132;
constexpr int NPC = 76;
constexpr int NWR = 125;
constexpr int EPC = 1280;
constexpr int THREADS = 512;
constexpr int MCAP = 31;
constexpr int SCHUNK = NCTA * 8;
constexpr int RCHUNK = 128 * 8;
constexpr int CAP = 2048;
constexpr int NSPILL = NWR * MCAP - CAP;

static_assert(NCTA * NPC >= NN, "nodes");
static_assert(NWR * EPC == EE, "edges");
static_assert(NN <= 16384 && EPC < 2047 && NPC < 80, "entry packing");

constexpr int SLOT = 5120;
constexpr int SM_RING = 0;
constexpr int SM_W12 = 0;
constexpr int SM_WOFF = 65536;
constexpr int SM_W3S = SM_WOFF + 4096;
constexpr int SM_OUT = 0;
constexpr int SM_EXT = 0;
constexpr int SM_AGG = 16 * SLOT;
constexpr int SM_WU = SM_AGG + 20480;
constexpr int SM_X = SM_WU + 65536;
constexpr int SM_ZL = SM_X + 8192;
constexpr int SM_Q = SM_X + 20480;
constexpr int SM_LIST = SM_Q + 20480;
constexpr int LISTB = (CAP + 64) * 4;
constexpr int SM_EID = SM_LIST + LISTB;
constexpr int SM_W3F = SM_EID + LISTB;
constexpr int SM_MISC = SM_W3F + 4096;
constexpr int SM_TRASH = SM_MISC + 2048;
constexpr int SM_TOTAL = SM_TRASH + 256;
constexpr int SM_ALLOC = SM_TOTAL;
static_assert(2 * LISTB >= SCHUNK * 16, "staging");
static_assert(SM_ALLOC <= 232448, "smem");

struct Misc {
    int cnt[NCTA];
    int ncnt[128];
    int off[100];
    int ovf;
    int anyovf;
    int total;
    int pad;
    int wovf[128];
    uint4 pad2;
    unsigned long long mbar[3];
};
constexpr int MISC_ZERO16 = 124;
static_assert(offsetof(Misc, mbar) == MISC_ZERO16 * 16, "misc layout");
static_assert(sizeof(Misc) <= 2048, "misc");

struct Scratch {
    uint4 P[NN * 16];
    uint4 mail[NCTA * RCHUNK];
    uint2 ovf[NWR * EPC];
    uint2 spill[NCTA * NSPILL];
    unsigned sync[64];
};
__device__ Scratch g_sc;

#define TSTAMP(i) do {} while (0)

__device__ __forceinline__ uint32_t smem_u32(const void* p) { return (uint32_t)__cvta_generic_to_shared(p); }

template <int ROWS>
__device__ __forceinline__ uint32_t sw(int row, int chunk) {
    return (uint32_t)((chunk >> 3) * (ROWS * 128) + row * 128 + (((chunk & 7) ^ (row & 7)) << 4));
}

__device__ __forceinline__ uint32_t w3sw(unsigned row, unsigned chunk) {
    return (chunk >> 3) * 2048 + row * 128 + (((chunk & 7) ^ ((row & 1) | ((row >> 1) & 6))) << 4);
}
__device__ __forceinline__ constexpr int r_off(int j) {
    return j < 4 ? SM_WU + j * 4096 : j < 8 ? SM_WU + 32768 + (j - 4) * 4096 : SM_X + (j - 8) * 4096;
}
__device__ __forceinline__ void cp16(uint32_t dst, const void* src) {
    asm volatile("cp.async.cg.shared.global [%0], [%1], 16;" ::"r"(dst), "l"(src) : "memory");
}
template <int SCALE, int OFF>
__device__ __forceinline__ void cp16g(uint32_t dst, const void* base, uint32_t idx, int skip) {
    asm volatile("{.reg .pred p; .reg .b64 a; mad.wide.u32 a, %2, %4, %1; setp.eq.s32 p, %3, 0;\n"
                 "@p cp.async.cg.shared.global [%0], [a+%5], 16;}"
                 ::"r"(dst), "l"(base), "r"(idx), "r"(skip), "n"(SCALE), "n"(OFF) : "memory");
}
__device__ __forceinline__ void cp_commit() { asm volatile("cp.async.commit_group;" ::: "memory"); }
template <int N>
__device__ __forceinline__ void cp_wait() { asm volatile("cp.async.wait_group %0;" ::"n"(N) : "memory"); }
template <int ID, int N>
__device__ __forceinline__ void bar_sync() { asm volatile("bar.sync %0, %1;" ::"n"(ID), "n"(N) : "memory"); }
template <int ID, int N>
__device__ __forceinline__ void bar_arrive() { asm volatile("bar.arrive %0, %1;" ::"n"(ID), "n"(N) : "memory"); }
__device__ __forceinline__ void fence_async() { asm volatile("fence.proxy.async.shared::cta;" ::: "memory"); }

__device__ __forceinline__ void ldsm4t(uint32_t (&r)[4], uint32_t a) {
    asm volatile("ldmatrix.sync.aligned.m8n8.x4.trans.shared.b16 {%0,%1,%2,%3}, [%4];"
                 : "=r"(r[0]), "=r"(r[1]), "=r"(r[2]), "=r"(r[3]) : "r"(a));
}
__device__ __forceinline__ uint4 lds128(uint32_t a) {
    uint4 v;
    asm volatile("ld.shared.v4.u32 {%0,%1,%2,%3}, [%4];" : "=r"(v.x), "=r"(v.y), "=r"(v.z), "=r"(v.w) : "r"(a));
    return v;
}
__device__ __forceinline__ uint2 lds64(uint32_t a) {
    uint2 v;
    asm volatile("ld.shared.v2.u32 {%0,%1}, [%2];" : "=r"(v.x), "=r"(v.y) : "r"(a));
    return v;
}
__device__ __forceinline__ uint32_t lds32(uint32_t a) {
    uint32_t v;
    asm volatile("ld.shared.u32 %0, [%1];" : "=r"(v) : "r"(a));
    return v;
}
__device__ __forceinline__ uint32_t lds16(uint32_t a) {
    uint32_t v;
    asm volatile("ld.shared.u16 %0, [%1];" : "=r"(v) : "r"(a));
    return v;
}
__device__ __forceinline__ void sts32(uint32_t a, uint32_t v) {
    asm volatile("st.shared.u32 [%0], %1;" ::"r"(a), "r"(v) : "memory");
}
__device__ __forceinline__ void stsm4t(uint32_t a, uint32_t r0, uint32_t r1, uint32_t r2, uint32_t r3) {
    asm volatile("stmatrix.sync.aligned.m8n8.x4.trans.shared.b16 [%0], {%1,%2,%3,%4};"
                 ::"r"(a), "r"(r0), "r"(r1), "r"(r2), "r"(r3) : "memory");
}
__device__ __forceinline__ void mma16(float (&d)[4], const uint32_t a0, const uint32_t a1, const uint32_t a2,
                                      const uint32_t a3, const uint32_t b0, const uint32_t b1) {
    asm("mma.sync.aligned.m16n8k16.row.col.f32.bf16.bf16.f32 {%0,%1,%2,%3}, {%4,%5,%6,%7}, {%8,%9}, {%0,%1,%2,%3};"
        : "+f"(d[0]), "+f"(d[1]), "+f"(d[2]), "+f"(d[3])
        : "r"(a0), "r"(a1), "r"(a2), "r"(a3), "r"(b0), "r"(b1));
}
__device__ __forceinline__ void mma8(float (&d)[4], const uint32_t a0, const uint32_t a1, const uint32_t b0) {
    asm("mma.sync.aligned.m16n8k8.row.col.f32.bf16.bf16.f32 {%0,%1,%2,%3}, {%4,%5}, {%6}, {%0,%1,%2,%3};"
        : "+f"(d[0]), "+f"(d[1]), "+f"(d[2]), "+f"(d[3])
        : "r"(a0), "r"(a1), "r"(b0));
}
__device__ __forceinline__ uint32_t movm(uint32_t a) {
    uint32_t d;
    asm("movmatrix.sync.aligned.m8n8.trans.b16 %0, %1;" : "=r"(d) : "r"(a));
    return d;
}
__device__ __forceinline__ void ldsm4tf(float (&r)[4], uint32_t a) {
    asm volatile("ldmatrix.sync.aligned.m8n8.x4.trans.shared.b16 {%0,%1,%2,%3}, [%4];"
                 : "=f"(r[0]), "=f"(r[1]), "=f"(r[2]), "=f"(r[3]) : "r"(a));
}
__device__ __forceinline__ int range_start(int r, int T) {
    const int t0 = ((r >> 2) * T) >> 2, n = ((((r >> 2) + 1) * T) >> 2) - t0, b = r & 3;
    return t0 + b * (n >> 2) + min(b, n & 3);
}
__device__ __forceinline__ uint32_t pack2(float lo, float hi) {
    uint32_t r;
    asm("cvt.rn.bf16x2.f32 %0, %1, %2;" : "=r"(r) : "f"(hi), "f"(lo));
    return r;
}
__device__ __forceinline__ uint32_t half2x(uint32_t a) {
    uint32_t r;
    asm("mul.rn.bf16x2 %0, %1, %2;" : "=r"(r) : "r"(a), "r"(0x3F003F00u));
    return r;
}
__device__ __forceinline__ float tanh_fast(float x) {
    float t;
    asm("tanh.approx.f32 %0, %1;" : "=f"(t) : "f"(x));
    return t;
}
__device__ __forceinline__ float silu_h(float h) { return fmaf(h, tanh_fast(h), h); }

__device__ __forceinline__ unsigned ld_relaxed32(const void* p) {
    unsigned v;
    asm volatile("ld.relaxed.gpu.global.u32 %0, [%1];" : "=r"(v) : "l"(p) : "memory");
    return v;
}
__device__ __forceinline__ unsigned ld_poll32(const void* p) {
    unsigned v;
    asm volatile("ld.acquire.gpu.global.u32 %0, [%1];" : "=r"(v) : "l"(p) : "memory");
    return v;
}
__device__ __forceinline__ uint32_t atoms_inc(uint32_t addr) {
    uint32_t r;
    asm volatile("atom.shared.add.u32 %0, [%1], 1;" : "=r"(r) : "r"(addr) : "memory");
    return r;
}
__device__ __forceinline__ void tma2d(uint32_t dst, const CUtensorMap* tm, int c0, int c1, uint32_t bar) {
    asm volatile("cp.async.bulk.tensor.2d.shared::cluster.global.mbarrier::complete_tx::bytes [%0], [%1, {%3, %4}], [%2];"
                 ::"r"(dst), "l"(tm), "r"(bar), "r"(c0), "r"(c1) : "memory");
}
__device__ __forceinline__ void tma_w(uint32_t dst, const CUtensorMap* tm, int row, uint32_t bar) {
    asm volatile("mbarrier.arrive.expect_tx.shared.b64 _, [%0], %1;" ::"r"(bar), "n"(32768) : "memory");
    tma2d(dst, tm, 0, row, bar);
    tma2d(dst + 32768, tm, 64, row, bar);
}
__device__ __forceinline__ void tma_store(const CUtensorMap* tm, uint32_t src, int c0, int c1) {
    asm volatile("cp.async.bulk.tensor.2d.global.shared::cta.bulk_group [%0, {%2, %3}], [%1];"
                 ::"l"(tm), "r"(src), "r"(c0), "r"(c1) : "memory");
}
__device__ __forceinline__ void mbar_wait(uint32_t bar) {
    uint32_t ok;
    int sp = 0;
    do {
        asm volatile("{.reg .pred p; mbarrier.try_wait.parity.shared.b64 p, [%1], 0; selp.u32 %0, 1, 0, p;}" : "=r"(ok) : "r"(bar) : "memory");
    } while (!ok && ++sp < (1 << 22));
}
template <int N>
__device__ __forceinline__ void cp_rows(uint32_t dst, const void* src) {
#pragma unroll
    for (int i = 0; i < N; i++)
        asm volatile("cp.async.cg.shared.global [%0], [%1], 16;" ::"r"(dst + i * 2048), "l"((const char*)src + i * 4096) : "memory");
}

#define ACC40(d)                                                                                              \
    "+f"(d[0]), "+f"(d[1]), "+f"(d[2]), "+f"(d[3]), "+f"(d[4]), "+f"(d[5]), "+f"(d[6]), "+f"(d[7]),         \
    "+f"(d[8]), "+f"(d[9]), "+f"(d[10]), "+f"(d[11]), "+f"(d[12]), "+f"(d[13]), "+f"(d[14]), "+f"(d[15]),   \
    "+f"(d[16]), "+f"(d[17]), "+f"(d[18]), "+f"(d[19]), "+f"(d[20]), "+f"(d[21]), "+f"(d[22]), "+f"(d[23]), \
    "+f"(d[24]), "+f"(d[25]), "+f"(d[26]), "+f"(d[27]), "+f"(d[28]), "+f"(d[29]), "+f"(d[30]), "+f"(d[31]), \
    "+f"(d[32]), "+f"(d[33]), "+f"(d[34]), "+f"(d[35]), "+f"(d[36]), "+f"(d[37]), "+f"(d[38]), "+f"(d[39])

__device__ __forceinline__ void wgmma_issue(float (&d)[40], uint32_t w_addr, uint32_t t_addr) {
    const uint32_t la = (w_addr >> 4) | 0x10000u, lb = (t_addr >> 4) | 0x10000u;
    asm volatile("wgmma.fence.sync.aligned;" ::: "memory");
#pragma unroll
    for (int ks = 0; ks < 8; ks++) {
        asm volatile(
            "{.reg .b64 da, db; .reg .pred p;\n"
            "setp.ne.s32 p, %43, 0;\n"
            "mov.b64 da, {%40, %42};\n"
            "mov.b64 db, {%41, %42};\n"
            "wgmma.mma_async.sync.aligned.m64n80k16.f32.bf16.bf16 "
            "{%0,%1,%2,%3,%4,%5,%6,%7,%8,%9,%10,%11,%12,%13,%14,%15,%16,%17,%18,%19,"
            "%20,%21,%22,%23,%24,%25,%26,%27,%28,%29,%30,%31,%32,%33,%34,%35,%36,%37,%38,%39},"
            "da, db, p, 1, 1, 1, 0;}"
            : ACC40(d)
            : "r"(la + ks * 128), "r"(lb + (ks >> 2) * 640 + (ks & 3) * 2), "r"(0x40000040u), "r"(ks > 0 ? 1 : 0));
    }
    asm volatile("wgmma.commit_group.sync.aligned;" ::: "memory");
}
#define ACC8(d, b) "+f"(d[b]), "+f"(d[b + 1]), "+f"(d[b + 2]), "+f"(d[b + 3]), "+f"(d[b + 4]), "+f"(d[b + 5]), "+f"(d[b + 6]), "+f"(d[b + 7])
__device__ __forceinline__ void wgmma_issue_split(float (&d)[40], uint32_t w_addr, uint32_t t_addr) {
    const uint32_t la = (w_addr >> 4) | 0x10000u, lb = (t_addr >> 4) | 0x10000u;
    asm volatile("wgmma.fence.sync.aligned;" ::: "memory");
#pragma unroll
    for (int ks = 0; ks < 8; ks++)
        asm volatile(
            "{.reg .b64 da, db;\n"
            "mov.b64 da, {%24, %26};\n"
            "mov.b64 db, {%25, %26};\n"
            "wgmma.mma_async.sync.aligned.m64n48k16.f32.bf16.bf16 "
            "{%0,%1,%2,%3,%4,%5,%6,%7,%8,%9,%10,%11,%12,%13,%14,%15,%16,%17,%18,%19,%20,%21,%22,%23},"
            "da, db, 1, 1, 1, 1, 0;}"
            : ACC8(d, 0), ACC8(d, 8), ACC8(d, 16)
            : "r"(la + ks * 128), "r"(lb + (ks >> 2) * 640 + (ks & 3) * 2), "r"(0x40000040u));
    asm volatile("wgmma.commit_group.sync.aligned;" ::: "memory");
#pragma unroll
    for (int ks = 0; ks < 8; ks++)
        asm volatile(
            "{.reg .b64 da, db;\n"
            "mov.b64 da, {%16, %18};\n"
            "mov.b64 db, {%17, %18};\n"
            "wgmma.mma_async.sync.aligned.m64n32k16.f32.bf16.bf16 "
            "{%0,%1,%2,%3,%4,%5,%6,%7,%8,%9,%10,%11,%12,%13,%14,%15},"
            "da, db, 1, 1, 1, 1, 0;}"
            : ACC8(d, 24), ACC8(d, 32)
            : "r"(la + ks * 128), "r"(lb + 384 + (ks >> 2) * 640 + (ks & 3) * 2), "r"(0x40000040u));
    asm volatile("wgmma.commit_group.sync.aligned;" ::: "memory");
}
template <int N>
__device__ __forceinline__ void wgmma_wait(float (&d)[40]) {
    asm volatile("wgmma.wait_group.sync.aligned %40;" : ACC40(d) : "n"(N) : "memory");
}
__device__ __forceinline__ void store_tile_half(uint32_t a, const float (&d)[40]) {
#pragma unroll
    for (int j = 0; j < 10; j += 2)
        stsm4t(a + j * 1024, half2x(pack2(d[4 * j], d[4 * j + 1])), half2x(pack2(d[4 * j + 2], d[4 * j + 3])),
               half2x(pack2(d[4 * j + 4], d[4 * j + 5])), half2x(pack2(d[4 * j + 6], d[4 * j + 7])));
}

template <int MODE>
__global__ void __launch_bounds__(THREADS, 1)
mpnn_kernel(const __nv_bfloat16* __restrict__ x, const __nv_bfloat16* __restrict__ e_attr,
            const int* __restrict__ src, const int* __restrict__ dst,
            const __nv_bfloat16* __restrict__ w_msg,
            Scratch* __restrict__ sc,
            const __grid_constant__ CUtensorMap tm_wm, const __grid_constant__ CUtensorMap tm_wu,
            const __grid_constant__ CUtensorMap tm_mail, const __grid_constant__ CUtensorMap tm_p,
            const __grid_constant__ CUtensorMap tm_out, const __grid_constant__ CUtensorMap tm_out2) {
    extern __shared__ __align__(1024) uint8_t smem[];
    const uint32_t sb = smem_u32(smem);
    Misc* ms = reinterpret_cast<Misc*>(smem + SM_MISC);
    const unsigned tid = threadIdx.x, lane = tid & 31;
    __builtin_assume(tid < THREADS);
    const int warp = __shfl_sync(0xffffffffu, tid >> 5, 0);
    const unsigned cta = blockIdx.x;
    __builtin_assume(cta < NCTA);
    if (tid == 0) TSTAMP(0);

    const unsigned g = lane >> 2, q = lane & 3;
    const int node0 = cta * NPC;
    const uint32_t tile_a = sw<80>(((lane >> 4) & 1) * 8 + (lane & 7), (warp & 7) * 2 + ((lane >> 3) & 1));

    if (warp >= 8) {
        const unsigned tb = tid - 256;
        __builtin_assume(tb < 256);
        const bool writer = (MODE & 1) && cta < NWR;
        uint32_t dv[5], sv[5];
        if (writer) {
            const int* dp = dst + cta * EPC;
            const int* sp = src + cta * EPC;
            asm volatile("ld.global.nc.v4.u32 {%0,%1,%2,%3}, [%4];" : "=r"(dv[0]), "=r"(dv[1]), "=r"(dv[2]), "=r"(dv[3]) : "l"(dp + tb * 4));
            asm volatile("ld.global.nc.u32 %0, [%1];" : "=r"(dv[4]) : "l"(dp + 1024 + tb));
            asm volatile("ld.global.nc.v4.u32 {%0,%1,%2,%3}, [%4];" : "=r"(sv[0]), "=r"(sv[1]), "=r"(sv[2]), "=r"(sv[3]) : "l"(sp + tb * 4));
            asm volatile("ld.global.nc.u32 %0, [%1];" : "=r"(sv[4]) : "l"(sp + 1024 + tb));
        }
        bar_arrive<3, 512>();
        unsigned htarget = 0;
        if (tb == 0 && MODE == 3) htarget = ld_relaxed32(&sc->sync[32]);
        if (tb == 32) asm volatile("prefetch.tensormap [%0];" ::"l"(&tm_mail) : "memory");
        if (tb < MISC_ZERO16) reinterpret_cast<uint4*>(ms)[tb] = make_uint4(0, 0, 0, 0);
        bar_sync<2, 256>();
        if (tb == 0) TSTAMP(17);
        if (warp == 8) asm volatile("bar.arrive %0, 288;" ::"r"(5 + (writer ? dv[0] >> 30 : 0)) : "memory");
        if (writer) {
            uint32_t own[5], pos[5];
#pragma unroll
            for (int i = 0; i < 5; i++) {
                own[i] = (dv[i] * 55189u) >> 22;
                pos[i] = atoms_inc(sb + SM_MISC + own[i] * 4);
            }
            if (tb == 0) TSTAMP(18);
            uint32_t pmax = 0;
#pragma unroll
            for (int i = 0; i < 5; i++) {
                const uint32_t nl = dv[i] - own[i] * NPC;
                const uint32_t el1 = i < 4 ? tb * 4 + i + 1 : tb + 1025;
                sts32(sb + SM_LIST + own[i] * 128 + (pos[i] < MCAP ? pos[i] * 4 + 4 : 0), (sv[i] * 128u + nl) * 2048u + el1);
                pmax = max(pmax, pos[i]);
            }
            if (pmax >= MCAP) {
#pragma unroll
                for (int i = 0; i < 5; i++) {
                    if (pos[i] >= MCAP) {
                        const int k = atomicAdd(&ms->ovf, 1);
                        sc->ovf[cta * EPC + k] = make_uint2(dv[i], cta * EPC + (i < 4 ? tb * 4 + i : tb + 1024));
                    }
                }
                __threadfence();
            }
            if (tb == 0) TSTAMP(8);
            bar_sync<2, 256>();
            if (tb == 0) TSTAMP(19);
            if (tb < NCTA) sts32(sb + SM_LIST + tb * 128, ((uint32_t)ms->ovf << 11) | (uint32_t)ms->cnt[tb]);
            fence_async();
            bar_sync<2, 256>();
            if (tb == 0) {
                tma_store(&tm_mail, sb + SM_LIST, cta * 32, 0);
                asm volatile("cp.async.bulk.commit_group;" ::: "memory");
                TSTAMP(9);
                asm volatile("cp.async.bulk.wait_group 0;" ::: "memory");
                TSTAMP(23);
            }
        }
        if (!(MODE & 2)) return;
        if (MODE == 3) {
            if (tb == 0) {
                asm volatile("red.release.gpu.global.add.u32 [%0], 1;" ::"l"(&sc->sync[32]) : "memory");
                htarget = htarget - htarget % NCTA + NCTA;
                int sp = 0;
                while ((int)(ld_poll32(&sc->sync[32]) - htarget) < 0 && ++sp < (1 << 22)) {}
                TSTAMP(24);
            }
            bar_sync<2, 256>();
        }
        uint32_t w[2][8];
        {
            const uint4* mine = sc->mail + cta * RCHUNK + (tb >> 2) * 8 + (tb & 3);
            const uint4* mine2 = tb + 256 < NWR * 4 ? mine + 512 : mine;
            asm volatile("ld.relaxed.gpu.global.v4.u32 {%0,%1,%2,%3}, [%16];\n"
                         "ld.relaxed.gpu.global.v4.u32 {%8,%9,%10,%11}, [%17];\n"
                         "ld.relaxed.gpu.global.v4.u32 {%4,%5,%6,%7}, [%16+64];\n"
                         "ld.relaxed.gpu.global.v4.u32 {%12,%13,%14,%15}, [%17+64];"
                         : "=r"(w[0][0]), "=r"(w[0][1]), "=r"(w[0][2]), "=r"(w[0][3]), "=r"(w[0][4]), "=r"(w[0][5]), "=r"(w[0][6]), "=r"(w[0][7]),
                           "=r"(w[1][0]), "=r"(w[1][1]), "=r"(w[1][2]), "=r"(w[1][3]), "=r"(w[1][4]), "=r"(w[1][5]), "=r"(w[1][6]), "=r"(w[1][7])
                         : "l"(mine), "l"(mine2) : "memory");
        }
        uint32_t hd[2];
        hd[0] = __shfl_sync(0xffffffffu, w[0][0], lane & ~3u);
        hd[1] = __shfl_sync(0xffffffffu, w[1][0], lane & ~3u);
        if (tb + 256 >= NWR * 4) hd[1] = 0;
        if (tb == 0) TSTAMP(10);
        int lim[2];
#pragma unroll
        for (int b = 0; b < 2; b++) {
            if ((hd[b] & 0x7ffu) > MCAP) { ms->wovf[(tb >> 2) + 64 * b] = hd[b] >> 11; ms->anyovf = 1; }
            lim[b] = (int)(hd[b] & 0x7ffu) - (int)(tb & 3) * 4;
        }
        const bool second = __any_sync(0xffffffffu, max(lim[0], lim[1]) >= 16);
        const uint32_t dummy = (96u + lane) << 11;
        if ((tb & 3) == 0) w[0][0] = w[1][0] = dummy;
        uint32_t rk[2][8];
        const uint32_t nc = smem_u32(ms->ncnt);
        auto hist = [&](int i0) {
#pragma unroll
            for (int b = 0; b < 2; b++)
#pragma unroll
                for (int i = i0; i < i0 + 4; i++) {
                    w[b][i] = lim[b] >= (i & 3) + (i >> 2) * 16 ? w[b][i] : dummy;
                    rk[b][i] = atoms_inc(nc + ((w[b][i] >> 9) & 0x1fc));
                }
        };
        hist(0);
        if (second) hist(4);
        const uint32_t wo = sb + SM_WOFF + (warp - 8) * 512;
        sts32(wo + 384 + lane * 4, 1u << 20);
        if (tb == 0) TSTAMP(20);
        bar_sync<2, 256>();
        int total;
        {
            const int c0 = lds32(nc + lane * 12), c1 = lds32(nc + lane * 12 + 4), c2 = lds32(nc + lane * 12 + 8);
            int s = c0 + c1 + c2;
#pragma unroll
            for (int d = 1; d < 32; d <<= 1) {
                const int t = __shfl_up_sync(0xffffffffu, s, d);
                if (lane >= d) s += t;
            }
            sts32(wo + lane * 12, s - c2 - c1 - c0);
            sts32(wo + lane * 12 + 4, s - c2 - c1);
            sts32(wo + lane * 12 + 8, s - c2);
            total = __shfl_sync(0xffffffffu, s, 31);
            if (warp == 15) {
                ms->off[lane * 3] = min(s - c2 - c1 - c0, CAP);
                ms->off[lane * 3 + 1] = min(s - c2 - c1, CAP);
                ms->off[lane * 3 + 2] = min(s - c2, CAP);
                if (lane == 31) { ms->off[96] = min(s, CAP); ms->total = s; if (s > CAP) ms->anyovf = 1; }
                if (total < CAP) {
                    const uint32_t pa = sb + SM_LIST + (total + lane) * 4;
                    sts32(pa, 79u << 23);
                    sts32(pa + LISTB, 0u);
                    if (lane < 16) sts32(pa + 128, 79u << 23);
                }
            }
            __syncwarp();
        }
        if (tb == 0) TSTAMP(22);
        const uint32_t eb = (tb >> 2) * EPC - 1;
        auto scatter = [&](int i0) {
#pragma unroll
            for (int b = 0; b < 2; b++)
#pragma unroll
                for (int i = i0; i < i0 + 4; i++) rk[b][i] += lds32(wo + ((w[b][i] >> 9) & 0x1fc));
#pragma unroll
            for (int b = 0; b < 2; b++)
#pragma unroll
                for (int i = i0; i < i0 + 4; i++) {
                    const uint32_t a = sb + SM_LIST + min(rk[b][i], (uint32_t)(CAP + 63)) * 4;
                    sts32(a, (w[b][i] >> 18) | ((w[b][i] << 12) & 0x3f800000u));
                    sts32(a + LISTB, eb + b * (64 * EPC) + (w[b][i] & 0x7ff));
                }
            if (total > CAP) {
#pragma unroll
                for (int b = 0; b < 2; b++)
#pragma unroll
                    for (int i = i0; i < i0 + 4; i++)
                        if (rk[b][i] >= CAP && rk[b][i] < (1u << 20))
                            sc->spill[cta * NSPILL + rk[b][i] - CAP] = make_uint2(node0 + ((w[b][i] >> 11) & 127), eb + b * (64 * EPC) + (w[b][i] & 0x7ff));
            }
        };
        scatter(0);
        if (second) scatter(4);
        if (tb == 0) TSTAMP(11);
    } else {
        unsigned target = 0;
        const uint32_t mb = smem_u32(ms->mbar);
        {
            const unsigned r0 = tid >> 4, c0 = tid & 15;
            bar_sync<3, 512>();
            cp_rows<8>(sb + SM_W12 + sw<256>(r0, c0), reinterpret_cast<const uint4*>(w_msg) + tid);
            cp16(sb + SM_W3S + w3sw(r0, c0), reinterpret_cast<const uint4*>(w_msg) + 4096 + tid);
            const uint32_t dx = sb + SM_X + sw<80>(r0, c0);
            const uint4* xg = reinterpret_cast<const uint4*>(x) + c0;
            if (tid == 32 && MODE == 3) target = ld_relaxed32(&sc->sync[0]);
            if (tid == 160) asm volatile("prefetch.tensormap [%0];" ::"l"(&tm_p) : "memory");
            if (tid == 64) asm volatile("prefetch.tensormap [%0];" ::"l"(&tm_wu) : "memory");
            if (tid == 96) asm volatile("prefetch.tensormap [%0];" ::"l"(&tm_out) : "memory");
            if (tid == 128) asm volatile("prefetch.tensormap [%0];" ::"l"(&tm_out2) : "memory");
            if (tid == 0) {
                asm volatile("mbarrier.init.shared.b64 [%0], 1;" ::"r"(mb) : "memory");
                asm volatile("mbarrier.init.shared.b64 [%0], 1;" ::"r"(mb + 8) : "memory");
                asm volatile("mbarrier.init.shared.b64 [%0], 1;" ::"r"(mb + 16) : "memory");
                asm volatile("fence.mbarrier_init.release.cluster;" ::: "memory");
                if (MODE & 2) {
                    tma_w(sb + SM_W12 + 16384, &tm_wm, 128, mb);
                    tma_w(sb + SM_WU, &tm_wu, 0, mb + 8);
                }
            }
#pragma unroll
            for (int i = 0; i < 2; i++) cp16(dx + i * 2048, xg + min(node0 + r0 + i * 16, (unsigned)(NN - 1)) * 16);
            bar_sync<5, 288>();
#pragma unroll
            for (int i = 2; i < 5; i++) cp16(dx + i * 2048, xg + min(node0 + r0 + i * 16, (unsigned)(NN - 1)) * 16);
            cp_commit();
        }
        const int wg = warp >> 2;
        float a0[40];
        cp_wait<0>();
        fence_async();
        target = target - target % NCTA + NCTA;
        if (tid == 32) sts32(sb + SM_TRASH, target);
        bar_sync<1, 256>();
        if (tid == 0) TSTAMP(1);
        if (MODE & 1) {
            wgmma_issue(a0, sb + SM_W12 + wg * 32768, sb + SM_X);
            wgmma_wait<0>(a0);
            if (tid == 0) TSTAMP(15);
            store_tile_half(sb + SM_AGG + tile_a, a0);
            fence_async();
            bar_sync<1, 256>();
            if (tid == 0) TSTAMP(16);
            if (tid == 0) {
                tma_store(&tm_p, sb + SM_AGG, 0, node0);
                tma_store(&tm_p, sb + SM_AGG + 10240, 64, node0);
                asm volatile("cp.async.bulk.commit_group;" ::: "memory");
            }
        }
        if (!(MODE & 2)) {
            asm volatile("cp.async.bulk.wait_group 0;" ::: "memory");
            return;
        }
        float a1[40];
        mbar_wait(mb);
        wgmma_issue(a0, sb + SM_W12 + wg * 32768 + 16384, sb + SM_X);
        mbar_wait(mb + 8);
        wgmma_issue(a1, sb + SM_WU + wg * 32768, sb + SM_X);
        wgmma_wait<0>(a0);
        asm volatile("" : ACC40(a1)::"memory");
        bar_sync<1, 256>();
        if (tid == 0) {
            if (MODE == 3) {
                TSTAMP(4);
                asm volatile("cp.async.bulk.wait_group 0;" ::: "memory");
                TSTAMP(2);
                asm volatile("red.release.gpu.global.add.u32 [%0], 1;" ::"l"(&sc->sync[0]) : "memory");
                TSTAMP(3);
            }
            if (cta < NWR)
                asm volatile("cp.async.bulk.prefetch.L2.global [%0], %1;"
                             ::"l"(reinterpret_cast<const char*>(e_attr) + (size_t)cta * (EPC * 32)), "n"(EPC * 32) : "memory");
        }
        store_tile_half(sb + SM_Q + tile_a, a0);
        {
            uint32_t f[4];
            const unsigned r = lane & 7, mat = lane >> 3;
            ldsm4t(f, sb + SM_W3S + w3sw(4 * (r >> 1) + (r & 1) + 2 * (mat >> 1), warp * 2 + (mat & 1)));
            reinterpret_cast<uint4*>(smem + SM_W3F)[tid] = make_uint4(half2x(f[0]), half2x(f[1]), half2x(f[2]), half2x(f[3]));
        }
#pragma unroll
        for (int j = 0; j < 10; j++)
            *reinterpret_cast<float4*>(smem + r_off(j) + tid * 16) = make_float4(a1[4 * j], a1[4 * j + 1], a1[4 * j + 2], a1[4 * j + 3]);
        if (tid >= 224) *reinterpret_cast<uint4*>(smem + SM_ZL + (lane >> 3) * 1024 + (lane & 7) * 16) = make_uint4(0, 0, 0, 0);
        if (tid == 0) TSTAMP(25);
        if (tid == 32 && MODE == 3) {
            TSTAMP(7);
            int sp = 0;
            while ((int)(ld_poll32(&sc->sync[0]) - target) < 0 && ++sp < (1 << 22)) {}
            TSTAMP(5);
        }
    }
    bar_sync<0, 512>();
    if (tid == 0) TSTAMP(6);

    const int M = ms->off[96];
    const int T = (M + 15) >> 4;
    const int rg = (warp & 3) * 4 + (warp >> 2);
    const int s = range_start(rg, T) * 16;
    const int e = min(range_start(rg + 1, T) * 16, M);
    const uint32_t ring = sb + SM_RING + rg * SLOT;
    {
        const unsigned fr = lane >> 3, fc = lane & 7;
        const char* Pb0 = reinterpret_cast<const char*>(sc->P) + ((fc ^ fr) << 4);
        const char* Pb1 = reinterpret_cast<const char*>(sc->P) + ((fc ^ fr ^ 4) << 4);
        const char* Eb = reinterpret_cast<const char*>(e_attr) + (lane & 1) * 16;
        asm volatile("" : "+l"(Pb0), "+l"(Pb1), "+l"(Eb));
        const uint32_t fdst = ring + lane * 16;
        const unsigned ledge = (lane & 6) | ((lane ^ (lane >> 3) ^ 1) & 1);
        const uint32_t lz = ((lane & 1) ? ring + ledge * 128 : sb + SM_ZL) + (((lane >> 4) ^ ledge) << 4);
        const uint32_t w3a = sb + SM_W3F + lane * 16;
        uint32_t sn[4], ei;
        auto fidx = [&](int tb) {
#pragma unroll
            for (int i = 0; i < 4; i++) sn[i] = lds16(sb + SM_LIST + (tb + fr) * 4 + i * 16);
            ei = lds32(sb + SM_EID + (tb + (lane >> 1)) * 4);
        };
        auto fetchP = [&](int h, int skip) {
#pragma unroll
            for (int i = 0; i < 4; i++) {
                if (h == 0) cp16g<256, 0>(fdst + i * 512, (i & 1) ? Pb1 : Pb0, sn[i], skip);
                else cp16g<256, 128>(fdst + 2048 + i * 512, (i & 1) ? Pb1 : Pb0, sn[i], skip);
            }
        };
        auto fetchE = [&](int skip) { cp16g<32, 0>(fdst + 4096, Eb, ei, skip); };
        int lo = s;
        auto first_fetch = [&]() {
            const int skip = lo >= e;
            fetchE(skip);
            fetchP(0, skip);
            cp_commit();
            fetchP(1, skip);
            cp_commit();
        };
        fidx(lo);
        if (warp >= 4) asm volatile("bar.sync %0, 256;" ::"r"(4 + (warp >> 2)) : "memory");
        first_fetch();
        if (warp < 12) asm volatile("bar.arrive %0, 256;" ::"r"(5 + (warp >> 2)) : "memory");
        if (tid == 480) tma_w(sb + SM_WU + 16384, &tm_wu, 128, smem_u32(ms->mbar) + 16);
        {
            const int nd = warp * 5 + min(lane, 4u);
            unsigned em = __ballot_sync(0xffffffffu, ms->off[nd] == ms->off[nd + 1]) & 31u;
            while (em) {
                const int k = __ffs(em) - 1;
                em &= em - 1;
                *reinterpret_cast<uint2*>(smem + SM_AGG + sw<80>(warp * 5 + k, lane >> 1) + (lane & 1) * 8) = make_uint2(0, 0);
            }
        }
            while (lo < e) {
            int tb = lo & ~15;
            const int nb = lds32(sb + SM_LIST + lo * 4) >> 23;
            const int hi = min(e, ms->off[min(nb + 8, 96)]);
            const int o0 = ms->off[nb + 2 * q];
            const uint32_t cn0 = ms->off[nb + 2 * q + 1] - o0;
            const uint32_t cn1 = ms->off[nb + 2 * q + 2] - o0 - cn0;
            uint32_t fa, fs;
            {
                const int nd = nb + (lane & 7);
                const int p0 = ms->off[nd], p1 = ms->off[nd + 1];
                const bool full = p0 >= s && p1 <= e && p1 > p0;
                const bool fst = p0 < s && p1 > s;
                const bool lst = p0 >= s && p0 < e && p1 > e;
                fa = full ? sb + SM_AGG + sw<80>(nd, lane >> 3)
                          : (fst ? ring + 4608 : lst ? ring + 4864 : sb + SM_TRASH) + (lane >> 3) * 16;
                fs = full ? 10240 : 128;
            }
            float acc[8][4];
#pragma unroll
            for (int m = 0; m < 8; m++)
#pragma unroll
                for (int k = 0; k < 4; k++) acc[m][k] = 0.f;
            uint32_t qf[4][4];
            const uint32_t qa = sb + SM_Q + sw<80>(min(nb + (int)(lane & 7), 79), lane >> 3);
#pragma unroll
            for (int j = 0; j < 4; j++) ldsm4t(qf[j], (qa ^ ((j & 1) << 6)) + (j >> 1) * 10240);
            uint32_t q0, q1, ss0, ss1;
            uint2 e0, e1;
            int last;
            float c[2][2][2][4];
            auto top = [&]() {
                const uint32_t u = tb + g - o0;
                q0 = (u < cn0 ? 0x3F80u : 0u) | (u - cn0 < cn1 ? 0x3F800000u : 0u);
                q1 = (u + 8 < cn0 ? 0x3F80u : 0u) | (u + 8 - cn0 < cn1 ? 0x3F800000u : 0u);
                tb += 16;
                fidx(tb);
                cp_wait<1>();
                __syncwarp();
                e0 = lds64(ring + 4096 + lane * 8);
                e1 = lds64(ring + 4096 + 256 + lane * 8);
            };
            auto stageA = [&](int j, float (&cc)[2][2][4]) {
                if (j == 2) { cp_wait<1>(); __syncwarp(); }
#pragma unroll
                for (int mm = 0; mm < 2; mm++) {
                    const int m = 2 * j + mm;
                    const uint4 wf = lds128(w3a + m * 512);
                    ldsm4tf(cc[mm][0], (lz ^ ((m & 3) << 5)) + (m >> 2) * 2048);
                    ldsm4tf(cc[mm][1], (lz ^ ((m & 3) << 5)) + (m >> 2) * 2048 + 1024);
                    mma8(cc[mm][0], qf[j][2 * mm], qf[j][2 * mm + 1], q0);
                    mma8(cc[mm][1], qf[j][2 * mm], qf[j][2 * mm + 1], q1);
                    mma16(cc[mm][0], wf.x, wf.y, wf.z, wf.w, e0.x, e0.y);
                    mma16(cc[mm][1], wf.x, wf.y, wf.z, wf.w, e1.x, e1.y);
                }
                if (j & 1) {
                    __syncwarp();
                    if (j == 1) fetchE(last);
                    fetchP(j >> 1, last);
                    cp_commit();
                }
            };
            auto stageB = [&](int j, float (&cc)[2][2][4]) {
#pragma unroll
                for (int mm = 0; mm < 2; mm++) {
                    const uint32_t a0 = pack2(silu_h(cc[mm][0][0]), silu_h(cc[mm][0][1]));
                    const uint32_t a1 = pack2(silu_h(cc[mm][0][2]), silu_h(cc[mm][0][3]));
                    const uint32_t a2 = pack2(silu_h(cc[mm][1][0]), silu_h(cc[mm][1][1]));
                    const uint32_t a3 = pack2(silu_h(cc[mm][1][2]), silu_h(cc[mm][1][3]));
                    mma16(acc[2 * j + mm], a0, a1, a2, a3, ss0, ss1);
                }
            };
            top();
            stageA(0, c[0]);
#pragma unroll 1
            for (;;) {
                ss0 = movm(q0);
                ss1 = movm(q1);
                last = tb >= hi;
                stageA(1, c[1]); stageB(0, c[0]);
                stageA(2, c[0]); stageB(1, c[1]);
                stageA(3, c[1]); stageB(2, c[0]);
                top();
                stageA(0, c[0]);
                stageB(3, c[1]);
                if (last) break;
            }
#pragma unroll
            for (int j = 0; j < 4; j++)
                stsm4t((fa ^ ((j & 1) << 6)) + (j >> 1) * fs, pack2(acc[2 * j][0], acc[2 * j][1]), pack2(acc[2 * j][2], acc[2 * j][3]),
                       pack2(acc[2 * j + 1][0], acc[2 * j + 1][1]), pack2(acc[2 * j + 1][2], acc[2 * j + 1][3]));
            lo = hi;
            if (lo < e) {
                cp_wait<0>();
                __syncwarp();
                fidx(lo & ~15);
                first_fetch();
            }
        }
    }
    if (warp >= 8) {
        const int tb = tid - 256;
        const int r1 = (warp - 8) * 2 + (lane >> 4);
        const unsigned hl = lane & 15;
        const int s1 = range_start(r1, T) * 16;
        const int e1 = min(range_start(r1 + 1, T) * 16, M);
        const int nl = lds32(sb + SM_LIST + max(e1 - 1, 0) * 4) >> 23;
        const int o1 = ms->off[nl + 1];
        const bool fx = s1 < e1 && ms->off[nl] >= s1 && o1 > e1;
        const bool slow = ms->anyovf;
        bar_sync<0, 512>();
        if (tb == 0) TSTAMP(21);
        if (fx) {
            uint4 u = lds128(sb + SM_RING + r1 * SLOT + 4864 + hl * 16);
            float v[8];
            v[0] = __uint_as_float(u.x << 16); v[1] = __uint_as_float(u.x & 0xffff0000u);
            v[2] = __uint_as_float(u.y << 16); v[3] = __uint_as_float(u.y & 0xffff0000u);
            v[4] = __uint_as_float(u.z << 16); v[5] = __uint_as_float(u.z & 0xffff0000u);
            v[6] = __uint_as_float(u.w << 16); v[7] = __uint_as_float(u.w & 0xffff0000u);
            int s2 = e1;
            for (int r2 = r1 + 1; s2 < o1; r2++) {
                const int e2 = range_start(r2 + 1, T) * 16;
                if (s2 < e2) {
                    u = lds128(sb + SM_RING + r2 * SLOT + 4608 + hl * 16);
                    v[0] += __uint_as_float(u.x << 16); v[1] += __uint_as_float(u.x & 0xffff0000u);
                    v[2] += __uint_as_float(u.y << 16); v[3] += __uint_as_float(u.y & 0xffff0000u);
                    v[4] += __uint_as_float(u.z << 16); v[5] += __uint_as_float(u.z & 0xffff0000u);
                    v[6] += __uint_as_float(u.w << 16); v[7] += __uint_as_float(u.w & 0xffff0000u);
                }
                s2 = e2;
            }
            *reinterpret_cast<uint4*>(smem + SM_AGG + sw<80>(nl, hl)) =
                make_uint4(pack2(v[0], v[1]), pack2(v[2], v[3]), pack2(v[4], v[5]), pack2(v[6], v[7]));
        }
        if (slow) {
            __threadfence();
            bar_sync<2, 256>();
            float* ext = reinterpret_cast<float*>(smem + SM_EXT);
            for (int i = tb; i < 80 * 128; i += 256) ext[i] = 0.f;
            bar_sync<2, 256>();
            const char* Pb = reinterpret_cast<const char*>(sc->P);
            for (int w = -1; w < NWR; w++) {
                const int cnt = w < 0 ? ms->total - CAP : ms->wovf[w];
                for (int k = warp - 8; k < cnt; k += 8) {
                    uint2 en;
                    const uint2* ep = w < 0 ? sc->spill + cta * NSPILL + k : sc->ovf + w * EPC + k;
                    asm volatile("ld.relaxed.gpu.global.v2.u32 {%0,%1}, [%2];" : "=r"(en.x), "=r"(en.y) : "l"(ep) : "memory");
                    const int nl = (int)en.x - node0;
                    const uint32_t eid = en.y;
                    if (nl < 0 || nl >= NPC) continue;
                    const uint32_t sn = src[eid];
                    for (int u = 0; u < 4; u++) {
                        const int f = lane * 4 + u;
                        float h = 0.f;
                        for (int kk = 0; kk < 16; kk++)
                            h = fmaf(__bfloat162float(e_attr[(size_t)eid * 16 + kk]), __bfloat162float(w_msg[(256 + kk) * 128 + f]), h);
                        h = 0.5f * h + __bfloat162float(*reinterpret_cast<const __nv_bfloat16*>(Pb + sn * 256 + f * 2)) +
                            __bfloat162float(*reinterpret_cast<const __nv_bfloat16*>(smem + SM_Q + sw<80>(nl, f >> 3) + (f & 7) * 2));
                        atomicAdd(&ext[nl * 128 + f], __bfloat162float(__float2bfloat16_rn(silu_h(h))));
                    }
                }
            }
            bar_sync<2, 256>();
            for (int i = tb; i < 80 * 128; i += 256) {
                const int r = i >> 7, f = i & 127;
                __nv_bfloat16* pp = reinterpret_cast<__nv_bfloat16*>(smem + SM_AGG + sw<80>(r, f >> 3) + (f & 7) * 2);
                *pp = __float2bfloat16_rn(__bfloat162float(*pp) + ext[i]);
            }
        }
        fence_async();
        bar_arrive<4, 512>();
        return;
    }
    {
        const int wg = warp >> 2;
        float a0[40];
        bar_arrive<0, 512>();
        fence_async();
#pragma unroll
        for (int j = 0; j < 10; j++) {
            const float4 v = *reinterpret_cast<const float4*>(smem + r_off(j) + tid * 16);
            a0[4 * j] = v.x; a0[4 * j + 1] = v.y; a0[4 * j + 2] = v.z; a0[4 * j + 3] = v.w;
        }
        mbar_wait(smem_u32(ms->mbar) + 16);
        bar_sync<4, 512>();
        if (tid == 0) TSTAMP(14);
        asm volatile("" : ACC40(a0)::"memory");
        wgmma_issue_split(a0, sb + SM_WU + wg * 32768 + 16384, sb + SM_AGG);
        auto emit = [&](int j0, int j1, const CUtensorMap* tm) {
#pragma unroll
            for (int j = j0; j < j1; j += 2) {
                uint32_t r[4];
#pragma unroll
                for (int k = 0; k < 4; k++) r[k] = pack2(silu_h(0.5f * a0[4 * j + 2 * k]), silu_h(0.5f * a0[4 * j + 2 * k + 1]));
                stsm4t(sb + SM_OUT + tile_a + j * 1024, r[0], r[1], r[2], r[3]);
            }
            fence_async();
            if (wg == 0) bar_sync<1, 128>(); else bar_sync<3, 128>();
            if ((tid & 127) == 0) {
                tma_store(tm, sb + SM_OUT + wg * 10240 + j0 * 1024, wg * 64, node0 + j0 * 8);
                asm volatile("cp.async.bulk.commit_group;" ::: "memory");
            }
        };
        asm volatile("wgmma.wait_group.sync.aligned 1;" : ACC8(a0, 0), ACC8(a0, 8), ACC8(a0, 16)::"memory");
        if (tid == 0) TSTAMP(26);
        emit(0, 6, &tm_out);
        asm volatile("wgmma.wait_group.sync.aligned 0;" : ACC8(a0, 24), ACC8(a0, 32)::"memory");
        emit(6, 10, &tm_out2);
        if ((tid & 127) == 0) asm volatile("cp.async.bulk.wait_group.read 0;" ::: "memory");
    }
    if (tid == 0) TSTAMP(12);
}

}

typedef CUresult (*EncodeFn)(CUtensorMap*, CUtensorMapDataType, cuuint32_t, void*, const cuuint64_t*, const cuuint64_t*,
                             const cuuint32_t*, const cuuint32_t*, CUtensorMapInterleave, CUtensorMapSwizzle,
                             CUtensorMapL2promotion, CUtensorMapFloatOOBfill);

static void make_map(EncodeFn enc, CUtensorMap* tm, const void* base, int rows, int box_rows) {
    const cuuint64_t dims[2] = {128, (cuuint64_t)rows};
    const cuuint64_t strides[1] = {256};
    const cuuint32_t box[2] = {64, (cuuint32_t)box_rows};
    const cuuint32_t estr[2] = {1, 1};
    enc(tm, CU_TENSOR_MAP_DATA_TYPE_BFLOAT16, 2, const_cast<void*>(base), dims, strides, box, estr, CU_TENSOR_MAP_INTERLEAVE_NONE,
        CU_TENSOR_MAP_SWIZZLE_128B, CU_TENSOR_MAP_L2_PROMOTION_NONE, CU_TENSOR_MAP_FLOAT_OOB_FILL_NONE);
}

extern "C" void kernel_launch(void* const* d_in, const int* in_sizes, int n_in, void* d_out, int out_size) {
    const __nv_bfloat16* x = (const __nv_bfloat16*)d_in[0];
    const __nv_bfloat16* e_attr = (const __nv_bfloat16*)d_in[1];
    const int* src = (const int*)d_in[2];
    const int* dst = (const int*)d_in[3];
    const __nv_bfloat16* w_msg = (const __nv_bfloat16*)d_in[4];

    static int fused = -1;
    static Scratch* sc = nullptr;
    static EncodeFn enc = nullptr;
    if (fused < 0) {
        cudaFuncSetAttribute(mpnn_kernel<1>, cudaFuncAttributeMaxDynamicSharedMemorySize, SM_ALLOC);
        cudaFuncSetAttribute(mpnn_kernel<2>, cudaFuncAttributeMaxDynamicSharedMemorySize, SM_ALLOC);
        cudaFuncSetAttribute(mpnn_kernel<3>, cudaFuncAttributeMaxDynamicSharedMemorySize, SM_ALLOC);
        int dev = 0, sms = 0, occ = 0;
        cudaGetDevice(&dev);
        cudaDeviceGetAttribute(&sms, cudaDevAttrMultiProcessorCount, dev);
        cudaOccupancyMaxActiveBlocksPerMultiprocessor(&occ, mpnn_kernel<3>, THREADS, SM_ALLOC);
        cudaGetSymbolAddress((void**)&sc, g_sc);
        cudaDriverEntryPointQueryResult qr;
        cudaGetDriverEntryPoint("cuTensorMapEncodeTiled", (void**)&enc, cudaEnableDefault, &qr);
        fused = (sms * occ >= NCTA) ? 1 : 0;
    }
    CUtensorMap tm_wm, tm_wu, tm_mail, tm_p, tm_out, tm_out2;
    make_map(enc, &tm_out, d_out, NN, 48);
    make_map(enc, &tm_out2, d_out, NN, NPC - 48);
    make_map(enc, &tm_p, sc->P, NN, NPC);
    {
        const cuuint64_t dims[2] = {RCHUNK * 4, NCTA};
        const cuuint64_t strides[1] = {RCHUNK * 16};
        const cuuint32_t box[2] = {32, NCTA};
        const cuuint32_t estr[2] = {1, 1};
        enc(&tm_mail, CU_TENSOR_MAP_DATA_TYPE_UINT32, 2, sc->mail, dims, strides, box, estr, CU_TENSOR_MAP_INTERLEAVE_NONE,
            CU_TENSOR_MAP_SWIZZLE_NONE, CU_TENSOR_MAP_L2_PROMOTION_NONE, CU_TENSOR_MAP_FLOAT_OOB_FILL_NONE);
    }
    make_map(enc, &tm_wm, d_in[4], 272, 128);
    make_map(enc, &tm_wu, d_in[5], 256, 128);
    if (fused) {
        mpnn_kernel<3><<<NCTA, THREADS, SM_ALLOC, cudaStreamPerThread>>>(x, e_attr, src, dst, w_msg, sc, tm_wm, tm_wu, tm_mail, tm_p, tm_out, tm_out2);
    } else {
        mpnn_kernel<1><<<NCTA, THREADS, SM_ALLOC, cudaStreamPerThread>>>(x, e_attr, src, dst, w_msg, sc, tm_wm, tm_wu, tm_mail, tm_p, tm_out, tm_out2);
        mpnn_kernel<2><<<NCTA, THREADS, SM_ALLOC, cudaStreamPerThread>>>(x, e_attr, src, dst, w_msg, sc, tm_wm, tm_wu, tm_mail, tm_p, tm_out, tm_out2);
    }
}
```

```cpp
#include <cuda_runtime.h>
#include <cuda.h>
#include <cuda_bf16.h>
#include <stdint.h>
#include <stddef.h>

namespace {

constexpr int NN = 10000;
constexpr int EE = 160000;
constexpr int NCTA = 132;
constexpr int NPC = 76;
constexpr int NWR = 125;
constexpr int EPC = 1280;
constexpr int THREADS = 512;
constexpr int MCAP = 31;
constexpr int SCHUNK = NCTA * 8;
constexpr int RCHUNK = 128 * 8;
constexpr int CAP = 2048;
constexpr int NSPILL = NWR * MCAP - CAP;

static_assert(NCTA * NPC >= NN, "nodes");
static_assert(NWR * EPC == EE, "edges");
static_assert(NN <= 16384 && EPC < 2047 && NPC < 80, "entry packing");

constexpr int SLOT = 5120;
constexpr int SM_RING = 0;
constexpr int SM_W12 = 0;
constexpr int SM_WOFF = 65536;
constexpr int SM_W3S = SM_WOFF + 4096;
constexpr int SM_OUT = 0;
constexpr int SM_EXT = 0;
constexpr int SM_AGG = 16 * SLOT;
constexpr int SM_WU = SM_AGG + 20480;
constexpr int SM_X = SM_WU + 65536;
constexpr int SM_ZL = SM_X + 8192;
constexpr int SM_Q = SM_X + 20480;
constexpr int SM_LIST = SM_Q + 20480;
constexpr int LISTB = (CAP + 64) * 4;
constexpr int SM_EID = SM_LIST + LISTB;
constexpr int SM_W3F = SM_EID + LISTB;
constexpr int SM_MISC = SM_W3F + 4096;
constexpr int SM_TRASH = SM_MISC + 2048;
constexpr int SM_TOTAL = SM_TRASH + 256;
constexpr int SM_ALLOC = SM_TOTAL;
static_assert(2 * LISTB >= SCHUNK * 16, "staging");
static_assert(SM_ALLOC <= 232448, "smem");

struct Misc {
    int cnt[NCTA];
    int ncnt[128];
    int off[100];
    int ovf;
    int anyovf;
    int total;
    int pad;
    int wovf[128];
    uint4 pad2;
    unsigned long long mbar[3];
};
constexpr int MISC_ZERO16 = 124;
static_assert(offsetof(Misc, mbar) == MISC_ZERO16 * 16, "misc layout");
static_assert(sizeof(Misc) <= 2048, "misc");

struct Scratch {
    uint4 P[NN * 16];
    uint4 mail[NCTA * RCHUNK];
    uint2 ovf[NWR * EPC];
    uint2 spill[NCTA * NSPILL];
    unsigned sync[64];
};
__device__ Scratch g_sc;

#define TSTAMP(i) do {} while (0)

__device__ __forceinline__ uint32_t smem_u32(const void* p) { return (uint32_t)__cvta_generic_to_shared(p); }

template <int ROWS>
__device__ __forceinline__ uint32_t sw(int row, int chunk) {
    return (uint32_t)((chunk >> 3) * (ROWS * 128) + row * 128 + (((chunk & 7) ^ (row & 7)) << 4));
}

__device__ __forceinline__ uint32_t w3sw(unsigned row, unsigned chunk) {
    return (chunk >> 3) * 2048 + row * 128 + (((chunk & 7) ^ ((row & 1) | ((row >> 1) & 6))) << 4);
}
__device__ __forceinline__ constexpr int r_off(int j) {
    return j < 4 ? SM_WU + j * 4096 : j < 8 ? SM_WU + 32768 + (j - 4) * 4096 : SM_X + (j - 8) * 4096;
}
__device__ __forceinline__ void cp16(uint32_t dst, const void* src) {
    asm volatile("cp.async.cg.shared.global [%0], [%1], 16;" ::"r"(dst), "l"(src) : "memory");
}
template <int SCALE, int OFF>
__device__ __forceinline__ void cp16g(uint32_t dst, const void* base, uint32_t idx, int skip) {
    asm volatile("{.reg .pred p; .reg .b64 a; mad.wide.u32 a, %2, %4, %1; setp.eq.s32 p, %3, 0;\n"
                 "@p cp.async.cg.shared.global [%0], [a+%5], 16;}"
                 ::"r"(dst), "l"(base), "r"(idx), "r"(skip), "n"(SCALE), "n"(OFF) : "memory");
}
__device__ __forceinline__ void cp_commit() { asm volatile("cp.async.commit_group;" ::: "memory"); }
template <int N>
__device__ __forceinline__ void cp_wait() { asm volatile("cp.async.wait_group %0;" ::"n"(N) : "memory"); }
template <int ID, int N>
__device__ __forceinline__ void bar_sync() { asm volatile("bar.sync %0, %1;" ::"n"(ID), "n"(N) : "memory"); }
template <int ID, int N>
__device__ __forceinline__ void bar_arrive() { asm volatile("bar.arrive %0, %1;" ::"n"(ID), "n"(N) : "memory"); }
__device__ __forceinline__ void fence_async() { asm volatile("fence.proxy.async.shared::cta;" ::: "memory"); }

__device__ __forceinline__ void ldsm4t(uint32_t (&r)[4], uint32_t a) {
    asm volatile("ldmatrix.sync.aligned.m8n8.x4.trans.shared.b16 {%0,%1,%2,%3}, [%4];"
                 : "=r"(r[0]), "=r"(r[1]), "=r"(r[2]), "=r"(r[3]) : "r"(a));
}
__device__ __forceinline__ uint4 lds128(uint32_t a) {
    uint4 v;
    asm volatile("ld.shared.v4.u32 {%0,%1,%2,%3}, [%4];" : "=r"(v.x), "=r"(v.y), "=r"(v.z), "=r"(v.w) : "r"(a));
    return v;
}
__device__ __forceinline__ uint2 lds64(uint32_t a) {
    uint2 v;
    asm volatile("ld.shared.v2.u32 {%0,%1}, [%2];" : "=r"(v.x), "=r"(v.y) : "r"(a));
    return v;
}
__device__ __forceinline__ uint32_t lds32(uint32_t a) {
    uint32_t v;
    asm volatile("ld.shared.u32 %0, [%1];" : "=r"(v) : "r"(a));
    return v;
}
__device__ __forceinline__ uint32_t lds16(uint32_t a) {
    uint32_t v;
    asm volatile("ld.shared.u16 %0, [%1];" : "=r"(v) : "r"(a));
    return v;
}
__device__ __forceinline__ void sts32(uint32_t a, uint32_t v) {
    asm volatile("st.shared.u32 [%0], %1;" ::"r"(a), "r"(v) : "memory");
}
__device__ __forceinline__ void stsm4t(uint32_t a, uint32_t r0, uint32_t r1, uint32_t r2, uint32_t r3) {
    asm volatile("stmatrix.sync.aligned.m8n8.x4.trans.shared.b16 [%0], {%1,%2,%3,%4};"
                 ::"r"(a), "r"(r0), "r"(r1), "r"(r2), "r"(r3) : "memory");
}
__device__ __forceinline__ void mma16(float (&d)[4], const uint32_t a0, const uint32_t a1, const uint32_t a2,
                                      const uint32_t a3, const uint32_t b0, const uint32_t b1) {
    asm("mma.sync.aligned.m16n8k16.row.col.f32.bf16.bf16.f32 {%0,%1,%2,%3}, {%4,%5,%6,%7}, {%8,%9}, {%0,%1,%2,%3};"
        : "+f"(d[0]), "+f"(d[1]), "+f"(d[2]), "+f"(d[3])
        : "r"(a0), "r"(a1), "r"(a2), "r"(a3), "r"(b0), "r"(b1));
}
__device__ __forceinline__ void mma8(float (&d)[4], const uint32_t a0, const uint32_t a1, const uint32_t b0) {
    asm("mma.sync.aligned.m16n8k8.row.col.f32.bf16.bf16.f32 {%0,%1,%2,%3}, {%4,%5}, {%6}, {%0,%1,%2,%3};"
        : "+f"(d[0]), "+f"(d[1]), "+f"(d[2]), "+f"(d[3])
        : "r"(a0), "r"(a1), "r"(b0));
}
__device__ __forceinline__ uint32_t movm(uint32_t a) {
    uint32_t d;
    asm("movmatrix.sync.aligned.m8n8.trans.b16 %0, %1;" : "=r"(d) : "r"(a));
    return d;
}
__device__ __forceinline__ void ldsm4tf(float (&r)[4], uint32_t a) {
    asm volatile("ldmatrix.sync.aligned.m8n8.x4.trans.shared.b16 {%0,%1,%2,%3}, [%4];"
                 : "=f"(r[0]), "=f"(r[1]), "=f"(r[2]), "=f"(r[3]) : "r"(a));
}
__device__ __forceinline__ int range_start(int r, int T) {
    const int t0 = ((r >> 2) * T) >> 2, n = ((((r >> 2) + 1) * T) >> 2) - t0, b = r & 3;
    return t0 + b * (n >> 2) + min(b, n & 3);
}
__device__ __forceinline__ uint32_t pack2(float lo, float hi) {
    uint32_t r;
    asm("cvt.rn.bf16x2.f32 %0, %1, %2;" : "=r"(r) : "f"(hi), "f"(lo));
    return r;
}
__device__ __forceinline__ uint32_t half2x(uint32_t a) {
    uint32_t r;
    asm("mul.rn.bf16x2 %0, %1, %2;" : "=r"(r) : "r"(a), "r"(0x3F003F00u));
    return r;
}
__device__ __forceinline__ float tanh_fast(float x) {
    float t;
    asm("tanh.approx.f32 %0, %1;" : "=f"(t) : "f"(x));
    return t;
}
__device__ __forceinline__ float silu_h(float h) { return fmaf(h, tanh_fast(h), h); }

__device__ __forceinline__ unsigned ld_relaxed32(const void* p) {
    unsigned v;
    asm volatile("ld.relaxed.gpu.global.u32 %0, [%1];" : "=r"(v) : "l"(p) : "memory");
    return v;
}
__device__ __forceinline__ unsigned ld_poll32(const void* p) {
    unsigned v;
    asm volatile("ld.acquire.gpu.global.u32 %0, [%1];" : "=r"(v) : "l"(p) : "memory");
    return v;
}
__device__ __forceinline__ uint32_t atoms_inc(uint32_t addr) {
    uint32_t r;
    asm volatile("atom.shared.add.u32 %0, [%1], 1;" : "=r"(r) : "r"(addr) : "memory");
    return r;
}
__device__ __forceinline__ void tma2d(uint32_t dst, const CUtensorMap* tm, int c0, int c1, uint32_t bar) {
    asm volatile("cp.async.bulk.tensor.2d.shared::cluster.global.mbarrier::complete_tx::bytes [%0], [%1, {%3, %4}], [%2];"
                 ::"r"(dst), "l"(tm), "r"(bar), "r"(c0), "r"(c1) : "memory");
}
__device__ __forceinline__ void tma_w(uint32_t dst, const CUtensorMap* tm, int row, uint32_t bar) {
    asm volatile("mbarrier.arrive.expect_tx.shared.b64 _, [%0], %1;" ::"r"(bar), "n"(32768) : "memory");
    tma2d(dst, tm, 0, row, bar);
    tma2d(dst + 32768, tm, 64, row, bar);
}
__device__ __forceinline__ void tma_store(const CUtensorMap* tm, uint32_t src, int c0, int c1) {
    asm volatile("cp.async.bulk.tensor.2d.global.shared::cta.bulk_group [%0, {%2, %3}], [%1];"
                 ::"l"(tm), "r"(src), "r"(c0), "r"(c1) : "memory");
}
__device__ __forceinline__ void mbar_wait(uint32_t bar) {
    uint32_t ok;
    int sp = 0;
    do {
        asm volatile("{.reg .pred p; mbarrier.try_wait.parity.shared.b64 p, [%1], 0; selp.u32 %0, 1, 0, p;}" : "=r"(ok) : "r"(bar) : "memory");
    } while (!ok && ++sp < (1 << 22));
}
template <int N>
__device__ __forceinline__ void cp_rows(uint32_t dst, const void* src) {
#pragma unroll
    for (int i = 0; i < N; i++)
        asm volatile("cp.async.cg.shared.global [%0], [%1], 16;" ::"r"(dst + i * 2048), "l"((const char*)src + i * 4096) : "memory");
}

#define ACC40(d)                                                                                              \
    "+f"(d[0]), "+f"(d[1]), "+f"(d[2]), "+f"(d[3]), "+f"(d[4]), "+f"(d[5]), "+f"(d[6]), "+f"(d[7]),         \
    "+f"(d[8]), "+f"(d[9]), "+f"(d[10]), "+f"(d[11]), "+f"(d[12]), "+f"(d[13]), "+f"(d[14]), "+f"(d[15]),   \
    "+f"(d[16]), "+f"(d[17]), "+f"(d[18]), "+f"(d[19]), "+f"(d[20]), "+f"(d[21]), "+f"(d[22]), "+f"(d[23]), \
    "+f"(d[24]), "+f"(d[25]), "+f"(d[26]), "+f"(d[27]), "+f"(d[28]), "+f"(d[29]), "+f"(d[30]), "+f"(d[31]), \
    "+f"(d[32]), "+f"(d[33]), "+f"(d[34]), "+f"(d[35]), "+f"(d[36]), "+f"(d[37]), "+f"(d[38]), "+f"(d[39])

__device__ __forceinline__ void wgmma_issue(float (&d)[40], uint32_t w_addr, uint32_t t_addr) {
    const uint32_t la = (w_addr >> 4) | 0x10000u, lb = (t_addr >> 4) | 0x10000u;
    asm volatile("wgmma.fence.sync.aligned;" ::: "memory");
#pragma unroll
    for (int ks = 0; ks < 8; ks++) {
        asm volatile(
            "{.reg .b64 da, db; .reg .pred p;\n"
            "setp.ne.s32 p, %43, 0;\n"
            "mov.b64 da, {%40, %42};\n"
            "mov.b64 db, {%41, %42};\n"
            "wgmma.mma_async.sync.aligned.m64n80k16.f32.bf16.bf16 "
            "{%0,%1,%2,%3,%4,%5,%6,%7,%8,%9,%10,%11,%12,%13,%14,%15,%16,%17,%18,%19,"
            "%20,%21,%22,%23,%24,%25,%26,%27,%28,%29,%30,%31,%32,%33,%34,%35,%36,%37,%38,%39},"
            "da, db, p, 1, 1, 1, 0;}"
            : ACC40(d)
            : "r"(la + ks * 128), "r"(lb + (ks >> 2) * 640 + (ks & 3) * 2), "r"(0x40000040u), "r"(ks > 0 ? 1 : 0));
    }
    asm volatile("wgmma.commit_group.sync.aligned;" ::: "memory");
}
#define ACC8(d, b) "+f"(d[b]), "+f"(d[b + 1]), "+f"(d[b + 2]), "+f"(d[b + 3]), "+f"(d[b + 4]), "+f"(d[b + 5]), "+f"(d[b + 6]), "+f"(d[b + 7])
__device__ __forceinline__ void wgmma_issue_split(float (&d)[40], uint32_t w_addr, uint32_t t_addr) {
    const uint32_t la = (w_addr >> 4) | 0x10000u, lb = (t_addr >> 4) | 0x10000u;
    asm volatile("wgmma.fence.sync.aligned;" ::: "memory");
#pragma unroll
    for (int ks = 0; ks < 8; ks++)
        asm volatile(
            "{.reg .b64 da, db;\n"
            "mov.b64 da, {%24, %26};\n"
            "mov.b64 db, {%25, %26};\n"
            "wgmma.mma_async.sync.aligned.m64n48k16.f32.bf16.bf16 "
            "{%0,%1,%2,%3,%4,%5,%6,%7,%8,%9,%10,%11,%12,%13,%14,%15,%16,%17,%18,%19,%20,%21,%22,%23},"
            "da, db, 1, 1, 1, 1, 0;}"
            : ACC8(d, 0), ACC8(d, 8), ACC8(d, 16)
            : "r"(la + ks * 128), "r"(lb + (ks >> 2) * 640 + (ks & 3) * 2), "r"(0x40000040u));
    asm volatile("wgmma.commit_group.sync.aligned;" ::: "memory");
#pragma unroll
    for (int ks = 0; ks < 8; ks++)
        asm volatile(
            "{.reg .b64 da, db;\n"
            "mov.b64 da, {%16, %18};\n"
            "mov.b64 db, {%17, %18};\n"
            "wgmma.mma_async.sync.aligned.m64n32k16.f32.bf16.bf16 "
            "{%0,%1,%2,%3,%4,%5,%6,%7,%8,%9,%10,%11,%12,%13,%14,%15},"
            "da, db, 1, 1, 1, 1, 0;}"
            : ACC8(d, 24), ACC8(d, 32)
            : "r"(la + ks * 128), "r"(lb + 384 + (ks >> 2) * 640 + (ks & 3) * 2), "r"(0x40000040u));
    asm volatile("wgmma.commit_group.sync.aligned;" ::: "memory");
}
template <int N>
__device__ __forceinline__ void wgmma_wait(float (&d)[40]) {
    asm volatile("wgmma.wait_group.sync.aligned %40;" : ACC40(d) : "n"(N) : "memory");
}
__device__ __forceinline__ void store_tile_half(uint32_t a, const float (&d)[40]) {
#pragma unroll
    for (int j = 0; j < 10; j += 2)
        stsm4t(a + j * 1024, half2x(pack2(d[4 * j], d[4 * j + 1])), half2x(pack2(d[4 * j + 2], d[4 * j + 3])),
               half2x(pack2(d[4 * j + 4], d[4 * j + 5])), half2x(pack2(d[4 * j + 6], d[4 * j + 7])));
}

template <int MODE>
__global__ void __launch_bounds__(THREADS, 1)
mpnn_kernel(const __nv_bfloat16* __restrict__ x, const __nv_bfloat16* __restrict__ e_attr,
            const int* __restrict__ src, const int* __restrict__ dst,
            const __nv_bfloat16* __restrict__ w_msg,
            Scratch* __restrict__ sc,
            const __grid_constant__ CUtensorMap tm_wm, const __grid_constant__ CUtensorMap tm_wu,
            const __grid_constant__ CUtensorMap tm_mail, const __grid_constant__ CUtensorMap tm_p,
            const __grid_constant__ CUtensorMap tm_out, const __grid_constant__ CUtensorMap tm_out2) {
    extern __shared__ __align__(1024) uint8_t smem[];
    const uint32_t sb = smem_u32(smem);
    Misc* ms = reinterpret_cast<Misc*>(smem + SM_MISC);
    const unsigned tid = threadIdx.x, lane = tid & 31;
    __builtin_assume(tid < THREADS);
    const unsigned cta = blockIdx.x;
    __builtin_assume(cta < NCTA);
    uint32_t dv[5], sv[5];
    if ((MODE & 1) && cta < NWR && tid >= 256) {
        const int* dp = dst + cta * EPC - 256;
        const int* sp = src + cta * EPC - 256;
        asm volatile("ld.global.nc.v4.u32 {%0,%1,%2,%3}, [%4];" : "=r"(dv[0]), "=r"(dv[1]), "=r"(dv[2]), "=r"(dv[3]) : "l"(dp - 768 + tid * 4));
        asm volatile("ld.global.nc.u32 %0, [%1];" : "=r"(dv[4]) : "l"(dp + 1024 + tid));
        asm volatile("ld.global.nc.v4.u32 {%0,%1,%2,%3}, [%4];" : "=r"(sv[0]), "=r"(sv[1]), "=r"(sv[2]), "=r"(sv[3]) : "l"(sp - 768 + tid * 4));
        asm volatile("ld.global.nc.u32 %0, [%1];" : "=r"(sv[4]) : "l"(sp + 1024 + tid));
    }
    const int warp = __shfl_sync(0xffffffffu, tid >> 5, 0);
    if (tid == 0) TSTAMP(0);

    const unsigned g = lane >> 2, q = lane & 3;
    const int node0 = cta * NPC;
    const uint32_t tile_a = sw<80>(((lane >> 4) & 1) * 8 + (lane & 7), (warp & 7) * 2 + ((lane >> 3) & 1));

    if (warp >= 8) {
        const unsigned tb = tid - 256;
        __builtin_assume(tb < 256);
        const bool writer = (MODE & 1) && cta < NWR;
        bar_arrive<3, 512>();
        unsigned htarget = 0;
        if (tb == 0 && MODE == 3) htarget = ld_relaxed32(&sc->sync[32]);
        if (tb == 32) asm volatile("prefetch.tensormap [%0];" ::"l"(&tm_mail) : "memory");
        if (tb < MISC_ZERO16) reinterpret_cast<uint4*>(ms)[tb] = make_uint4(0, 0, 0, 0);
        bar_sync<2, 256>();
        if (tb == 0) TSTAMP(17);
        if (warp == 8) asm volatile("bar.arrive %0, 288;" ::"r"(5 + (writer ? dv[0] >> 30 : 0)) : "memory");
        if (writer) {
            uint32_t own[5], pos[5];
#pragma unroll
            for (int i = 0; i < 5; i++) {
                own[i] = (dv[i] * 55189u) >> 22;
                pos[i] = atoms_inc(sb + SM_MISC + own[i] * 4);
            }
            if (tb == 0) TSTAMP(18);
            uint32_t pmax = 0;
#pragma unroll
            for (int i = 0; i < 5; i++) {
                const uint32_t nl = dv[i] - own[i] * NPC;
                const uint32_t el1 = i < 4 ? tb * 4 + i + 1 : tb + 1025;
                sts32(sb + SM_LIST + own[i] * 128 + (pos[i] < MCAP ? pos[i] * 4 + 4 : 0), (sv[i] * 128u + nl) * 2048u + el1);
                pmax = max(pmax, pos[i]);
            }
            if (pmax >= MCAP) {
#pragma unroll
                for (int i = 0; i < 5; i++) {
                    if (pos[i] >= MCAP) {
                        const int k = atomicAdd(&ms->ovf, 1);
                        sc->ovf[cta * EPC + k] = make_uint2(dv[i], cta * EPC + (i < 4 ? tb * 4 + i : tb + 1024));
                    }
                }
                __threadfence();
            }
            if (tb == 0) TSTAMP(8);
            bar_sync<2, 256>();
            if (tb == 0) TSTAMP(19);
            if (tb < NCTA) sts32(sb + SM_LIST + tb * 128, ((uint32_t)ms->ovf << 11) | (uint32_t)ms->cnt[tb]);
            fence_async();
            bar_sync<2, 256>();
            if (tb == 0) {
                tma_store(&tm_mail, sb + SM_LIST, cta * 32, 0);
                asm volatile("cp.async.bulk.commit_group;" ::: "memory");
                TSTAMP(9);
                asm volatile("cp.async.bulk.wait_group 0;" ::: "memory");
                TSTAMP(23);
            }
        }
        if (!(MODE & 2)) return;
        if (MODE == 3) {
            if (tb == 0) {
                asm volatile("red.release.gpu.global.add.u32 [%0], 1;" ::"l"(&sc->sync[32]) : "memory");
                htarget = htarget - htarget % NCTA + NCTA;
                int sp = 0;
                while ((int)(ld_poll32(&sc->sync[32]) - htarget) < 0 && ++sp < (1 << 22)) {}
                TSTAMP(24);
            }
            bar_sync<2, 256>();
        }
        uint32_t w[2][8];
        {
            const uint4* mine = sc->mail + cta * RCHUNK + (tb >> 2) * 8 + (tb & 3);
            const uint4* mine2 = tb + 256 < NWR * 4 ? mine + 512 : mine;
            asm volatile("ld.relaxed.gpu.global.v4.u32 {%0,%1,%2,%3}, [%16];\n"
                         "ld.relaxed.gpu.global.v4.u32 {%8,%9,%10,%11}, [%17];\n"
                         "ld.relaxed.gpu.global.v4.u32 {%4,%5,%6,%7}, [%16+64];\n"
                         "ld.relaxed.gpu.global.v4.u32 {%12,%13,%14,%15}, [%17+64];"
                         : "=r"(w[0][0]), "=r"(w[0][1]), "=r"(w[0][2]), "=r"(w[0][3]), "=r"(w[0][4]), "=r"(w[0][5]), "=r"(w[0][6]), "=r"(w[0][7]),
                           "=r"(w[1][0]), "=r"(w[1][1]), "=r"(w[1][2]), "=r"(w[1][3]), "=r"(w[1][4]), "=r"(w[1][5]), "=r"(w[1][6]), "=r"(w[1][7])
                         : "l"(mine), "l"(mine2) : "memory");
        }
        uint32_t hd[2];
        hd[0] = __shfl_sync(0xffffffffu, w[0][0], lane & ~3u);
        hd[1] = __shfl_sync(0xffffffffu, w[1][0], lane & ~3u);
        if (tb + 256 >= NWR * 4) hd[1] = 0;
        if (tb == 0) TSTAMP(10);
        int lim[2];
#pragma unroll
        for (int b = 0; b < 2; b++) {
            if ((hd[b] & 0x7ffu) > MCAP) { ms->wovf[(tb >> 2) + 64 * b] = hd[b] >> 11; ms->anyovf = 1; }
            lim[b] = (int)(hd[b] & 0x7ffu) - (int)(tb & 3) * 4;
        }
        const bool second = __any_sync(0xffffffffu, max(lim[0], lim[1]) >= 16);
        const uint32_t dummy = (96u + lane) << 11;
        if ((tb & 3) == 0) w[0][0] = w[1][0] = dummy;
        uint32_t rk[2][8];
        const uint32_t nc = smem_u32(ms->ncnt);
        auto hist = [&](int i0) {
#pragma unroll
            for (int b = 0; b < 2; b++)
#pragma unroll
                for (int i = i0; i < i0 + 4; i++) {
                    w[b][i] = lim[b] >= (i & 3) + (i >> 2) * 16 ? w[b][i] : dummy;
                    rk[b][i] = atoms_inc(nc + ((w[b][i] >> 9) & 0x1fc));
                }
        };
        hist(0);
        if (second) hist(4);
        const uint32_t wo = sb + SM_WOFF + (warp - 8) * 512;
        sts32(wo + 384 + lane * 4, 1u << 20);
        if (tb == 0) TSTAMP(20);
        bar_sync<2, 256>();
        int total;
        {
            const int c0 = lds32(nc + lane * 12), c1 = lds32(nc + lane * 12 + 4), c2 = lds32(nc + lane * 12 + 8);
            int s = c0 + c1 + c2;
#pragma unroll
            for (int d = 1; d < 32; d <<= 1) {
                const int t = __shfl_up_sync(0xffffffffu, s, d);
                if (lane >= d) s += t;
            }
            sts32(wo + lane * 12, s - c2 - c1 - c0);
            sts32(wo + lane * 12 + 4, s - c2 - c1);
            sts32(wo + lane * 12 + 8, s - c2);
            total = __shfl_sync(0xffffffffu, s, 31);
            if (warp == 15) {
                ms->off[lane * 3] = min(s - c2 - c1 - c0, CAP);
                ms->off[lane * 3 + 1] = min(s - c2 - c1, CAP);
                ms->off[lane * 3 + 2] = min(s - c2, CAP);
                if (lane == 31) { ms->off[96] = min(s, CAP); ms->total = s; if (s > CAP) ms->anyovf = 1; }
                if (total < CAP) {
                    const uint32_t pa = sb + SM_LIST + (total + lane) * 4;
                    sts32(pa, 79u << 23);
                    sts32(pa + LISTB, 0u);
                    if (lane < 16) sts32(pa + 128, 79u << 23);
                }
            }
            __syncwarp();
        }
        if (tb == 0) TSTAMP(22);
        const uint32_t eb = (tb >> 2) * EPC - 1;
        auto scatter = [&](int i0) {
#pragma unroll
            for (int b = 0; b < 2; b++)
#pragma unroll
                for (int i = i0; i < i0 + 4; i++) rk[b][i] += lds32(wo + ((w[b][i] >> 9) & 0x1fc));
#pragma unroll
            for (int b = 0; b < 2; b++)
#pragma unroll
                for (int i = i0; i < i0 + 4; i++) {
                    const uint32_t a = sb + SM_LIST + min(rk[b][i], (uint32_t)(CAP + 63)) * 4;
                    sts32(a, (w[b][i] >> 18) | ((w[b][i] << 12) & 0x3f800000u));
                    sts32(a + LISTB, eb + b * (64 * EPC) + (w[b][i] & 0x7ff));
                }
            if (total > CAP) {
#pragma unroll
                for (int b = 0; b < 2; b++)
#pragma unroll
                    for (int i = i0; i < i0 + 4; i++)
                        if (rk[b][i] >= CAP && rk[b][i] < (1u << 20))
                            sc->spill[cta * NSPILL + rk[b][i] - CAP] = make_uint2(node0 + ((w[b][i] >> 11) & 127), eb + b * (64 * EPC) + (w[b][i] & 0x7ff));
            }
        };
        scatter(0);
        if (second) scatter(4);
        if (tb == 0) TSTAMP(11);
    } else {
        unsigned target = 0;
        const uint32_t mb = smem_u32(ms->mbar);
        {
            const unsigned r0 = tid >> 4, c0 = tid & 15;
            bar_sync<3, 512>();
            cp_rows<8>(sb + SM_W12 + sw<256>(r0, c0), reinterpret_cast<const uint4*>(w_msg) + tid);
            cp16(sb + SM_W3S + w3sw(r0, c0), reinterpret_cast<const uint4*>(w_msg) + 4096 + tid);
            const uint32_t dx = sb + SM_X + sw<80>(r0, c0);
            const uint4* xg = reinterpret_cast<const uint4*>(x) + c0;
            if (tid == 32 && MODE == 3) target = ld_relaxed32(&sc->sync[0]);
            if (tid == 160) asm volatile("prefetch.tensormap [%0];" ::"l"(&tm_p) : "memory");
            if (tid == 64) asm volatile("prefetch.tensormap [%0];" ::"l"(&tm_wu) : "memory");
            if (tid == 96) asm volatile("prefetch.tensormap [%0];" ::"l"(&tm_out) : "memory");
            if (tid == 128) asm volatile("prefetch.tensormap [%0];" ::"l"(&tm_out2) : "memory");
            if (tid == 0) {
                asm volatile("mbarrier.init.shared.b64 [%0], 1;" ::"r"(mb) : "memory");
                asm volatile("mbarrier.init.shared.b64 [%0], 1;" ::"r"(mb + 8) : "memory");
                asm volatile("mbarrier.init.shared.b64 [%0], 1;" ::"r"(mb + 16) : "memory");
                asm volatile("fence.mbarrier_init.release.cluster;" ::: "memory");
                if (MODE & 2) {
                    tma_w(sb + SM_W12 + 16384, &tm_wm, 128, mb);
                    tma_w(sb + SM_WU, &tm_wu, 0, mb + 8);
                }
            }
#pragma unroll
            for (int i = 0; i < 2; i++) cp16(dx + i * 2048, xg + min(node0 + r0 + i * 16, (unsigned)(NN - 1)) * 16);
            bar_sync<5, 288>();
#pragma unroll
            for (int i = 2; i < 5; i++) cp16(dx + i * 2048, xg + min(node0 + r0 + i * 16, (unsigned)(NN - 1)) * 16);
            cp_commit();
        }
        const int wg = warp >> 2;
        float a0[40];
        cp_wait<0>();
        fence_async();
        target = target - target % NCTA + NCTA;
        if (tid == 32) sts32(sb + SM_TRASH, target);
        bar_sync<1, 256>();
        if (tid == 0) TSTAMP(1);
        if (MODE & 1) {
            wgmma_issue(a0, sb + SM_W12 + wg * 32768, sb + SM_X);
            wgmma_wait<0>(a0);
            if (tid == 0) TSTAMP(15);
            store_tile_half(sb + SM_AGG + tile_a, a0);
            fence_async();
            bar_sync<1, 256>();
            if (tid == 0) TSTAMP(16);
            if (tid == 0) {
                tma_store(&tm_p, sb + SM_AGG, 0, node0);
                tma_store(&tm_p, sb + SM_AGG + 10240, 64, node0);
                asm volatile("cp.async.bulk.commit_group;" ::: "memory");
            }
        }
        if (!(MODE & 2)) {
            asm volatile("cp.async.bulk.wait_group 0;" ::: "memory");
            return;
        }
        float a1[40];
        mbar_wait(mb);
        wgmma_issue(a0, sb + SM_W12 + wg * 32768 + 16384, sb + SM_X);
        mbar_wait(mb + 8);
        wgmma_issue(a1, sb + SM_WU + wg * 32768, sb + SM_X);
        wgmma_wait<0>(a0);
        asm volatile("" : ACC40(a1)::"memory");
        bar_sync<1, 256>();
        if (tid == 0) {
            if (MODE == 3) {
                TSTAMP(4);
                asm volatile("cp.async.bulk.wait_group 0;" ::: "memory");
                TSTAMP(2);
                asm volatile("red.release.gpu.global.add.u32 [%0], 1;" ::"l"(&sc->sync[0]) : "memory");
                TSTAMP(3);
            }
            if (cta < NWR)
                asm volatile("cp.async.bulk.prefetch.L2.global [%0], %1;"
                             ::"l"(reinterpret_cast<const char*>(e_attr) + (size_t)cta * (EPC * 32)), "n"(EPC * 32) : "memory");
        }
        store_tile_half(sb + SM_Q + tile_a, a0);
        {
            uint32_t f[4];
            const unsigned r = lane & 7, mat = lane >> 3;
            ldsm4t(f, sb + SM_W3S + w3sw(4 * (r >> 1) + (r & 1) + 2 * (mat >> 1), warp * 2 + (mat & 1)));
            reinterpret_cast<uint4*>(smem + SM_W3F)[tid] = make_uint4(half2x(f[0]), half2x(f[1]), half2x(f[2]), half2x(f[3]));
        }
#pragma unroll
        for (int j = 0; j < 10; j++)
            *reinterpret_cast<float4*>(smem + r_off(j) + tid * 16) = make_float4(a1[4 * j], a1[4 * j + 1], a1[4 * j + 2], a1[4 * j + 3]);
        if (tid >= 224) *reinterpret_cast<uint4*>(smem + SM_ZL + (lane >> 3) * 1024 + (lane & 7) * 16) = make_uint4(0, 0, 0, 0);
        if (tid == 0) TSTAMP(25);
        if (tid == 32 && MODE == 3) {
            TSTAMP(7);
            int sp = 0;
            while ((int)(ld_poll32(&sc->sync[0]) - target) < 0 && ++sp < (1 << 22)) {}
            TSTAMP(5);
        }
    }
    bar_sync<0, 512>();
    if (tid == 0) TSTAMP(6);

    const int M = ms->off[96];
    const int T = (M + 15) >> 4;
    const int rg = (warp & 3) * 4 + (warp >> 2);
    const int s = range_start(rg, T) * 16;
    const int e = min(range_start(rg + 1, T) * 16, M);
    const uint32_t ring = sb + SM_RING + rg * SLOT;
    {
        const unsigned fr = lane >> 3, fc = lane & 7;
        const char* Pb0 = reinterpret_cast<const char*>(sc->P) + ((fc ^ fr) << 4);
        const char* Pb1 = reinterpret_cast<const char*>(sc->P) + ((fc ^ fr ^ 4) << 4);
        const char* Eb = reinterpret_cast<const char*>(e_attr) + (lane & 1) * 16;
        asm volatile("" : "+l"(Pb0), "+l"(Pb1), "+l"(Eb));
        const uint32_t fdst = ring + lane * 16;
        const unsigned ledge = (lane & 6) | ((lane ^ (lane >> 3) ^ 1) & 1);
        const uint32_t lz = ((lane & 1) ? ring + ledge * 128 : sb + SM_ZL) + (((lane >> 4) ^ ledge) << 4);
        const uint32_t w3a = sb + SM_W3F + lane * 16;
        uint32_t sn[4], ei;
        auto fidx = [&](int tb) {
#pragma unroll
            for (int i = 0; i < 4; i++) sn[i] = lds16(sb + SM_LIST + (tb + fr) * 4 + i * 16);
            ei = lds32(sb + SM_EID + (tb + (lane >> 1)) * 4);
        };
        auto fetchP = [&](int h, int skip) {
#pragma unroll
            for (int i = 0; i < 4; i++) {
                if (h == 0) cp16g<256, 0>(fdst + i * 512, (i & 1) ? Pb1 : Pb0, sn[i], skip);
                else cp16g<256, 128>(fdst + 2048 + i * 512, (i & 1) ? Pb1 : Pb0, sn[i], skip);
            }
        };
        auto fetchE = [&](int skip) { cp16g<32, 0>(fdst + 4096, Eb, ei, skip); };
        int lo = s;
        auto first_fetch = [&]() {
            const int skip = lo >= e;
            fetchE(skip);
            fetchP(0, skip);
            cp_commit();
            fetchP(1, skip);
            cp_commit();
        };
        fidx(lo);
        if (warp >= 4) asm volatile("bar.sync %0, 256;" ::"r"(4 + (warp >> 2)) : "memory");
        fetchE(lo >= e);
        fetchP(0, lo >= e);
        cp_commit();
        if (warp < 12) asm volatile("bar.arrive %0, 256;" ::"r"(5 + (warp >> 2)) : "memory");
        fetchP(1, lo >= e);
        cp_commit();
        if (tid == 480) tma_w(sb + SM_WU + 16384, &tm_wu, 128, smem_u32(ms->mbar) + 16);
        {
            const int nd = warp * 5 + min(lane, 4u);
            unsigned em = __ballot_sync(0xffffffffu, ms->off[nd] == ms->off[nd + 1]) & 31u;
            while (em) {
                const int k = __ffs(em) - 1;
                em &= em - 1;
                *reinterpret_cast<uint2*>(smem + SM_AGG + sw<80>(warp * 5 + k, lane >> 1) + (lane & 1) * 8) = make_uint2(0, 0);
            }
        }
        while (lo < e) {
            int tb = lo & ~15;
            const int nb = lds32(sb + SM_LIST + lo * 4) >> 23;
            const int hi = min(e, ms->off[min(nb + 8, 96)]);
            const int o0 = ms->off[nb + 2 * q];
            const uint32_t cn0 = ms->off[nb + 2 * q + 1] - o0;
            const uint32_t cn1 = ms->off[nb + 2 * q + 2] - o0 - cn0;
            uint32_t fa, fs;
            {
                const int nd = nb + (lane & 7);
                const int p0 = ms->off[nd], p1 = ms->off[nd + 1];
                const bool full = p0 >= s && p1 <= e && p1 > p0;
                const bool fst = p0 < s && p1 > s;
                const bool lst = p0 >= s && p0 < e && p1 > e;
                fa = full ? sb + SM_AGG + sw<80>(nd, lane >> 3)
                          : (fst ? ring + 4608 : lst ? ring + 4864 : sb + SM_TRASH) + (lane >> 3) * 16;
                fs = full ? 10240 : 128;
            }
            float acc[8][4];
#pragma unroll
            for (int m = 0; m < 8; m++)
#pragma unroll
                for (int k = 0; k < 4; k++) acc[m][k] = 0.f;
            uint32_t qf[4][4];
            const uint32_t qa = sb + SM_Q + sw<80>(min(nb + (int)(lane & 7), 79), lane >> 3);
#pragma unroll
            for (int j = 0; j < 4; j++) ldsm4t(qf[j], (qa ^ ((j & 1) << 6)) + (j >> 1) * 10240);
            uint32_t q0, q1, ss0, ss1;
            uint2 e0, e1;
            int last;
            float c[2][2][2][4];
            auto top = [&]() {
                const uint32_t u = tb + g - o0;
                q0 = (u < cn0 ? 0x3F80u : 0u) | (u - cn0 < cn1 ? 0x3F800000u : 0u);
                q1 = (u + 8 < cn0 ? 0x3F80u : 0u) | (u + 8 - cn0 < cn1 ? 0x3F800000u : 0u);
                tb += 16;
                fidx(tb);
                cp_wait<1>();
                __syncwarp();
                e0 = lds64(ring + 4096 + lane * 8);
                e1 = lds64(ring + 4096 + 256 + lane * 8);
            };
            auto stageA = [&](int j, float (&cc)[2][2][4]) {
                if (j == 2) { cp_wait<1>(); __syncwarp(); }
#pragma unroll
                for (int mm = 0; mm < 2; mm++) {
                    const int m = 2 * j + mm;
                    const uint4 wf = lds128(w3a + m * 512);
                    ldsm4tf(cc[mm][0], (lz ^ ((m & 3) << 5)) + (m >> 2) * 2048);
                    ldsm4tf(cc[mm][1], (lz ^ ((m & 3) << 5)) + (m >> 2) * 2048 + 1024);
                    mma8(cc[mm][0], qf[j][2 * mm], qf[j][2 * mm + 1], q0);
                    mma8(cc[mm][1], qf[j][2 * mm], qf[j][2 * mm + 1], q1);
                    mma16(cc[mm][0], wf.x, wf.y, wf.z, wf.w, e0.x, e0.y);
                    mma16(cc[mm][1], wf.x, wf.y, wf.z, wf.w, e1.x, e1.y);
                }
                if (j & 1) {
                    __syncwarp();
                    if (j == 1) fetchE(last);
                    fetchP(j >> 1, last);
                    cp_commit();
                }
            };
            auto stageB = [&](int j, float (&cc)[2][2][4]) {
#pragma unroll
                for (int mm = 0; mm < 2; mm++) {
                    const uint32_t a0 = pack2(silu_h(cc[mm][0][0]), silu_h(cc[mm][0][1]));
                    const uint32_t a1 = pack2(silu_h(cc[mm][0][2]), silu_h(cc[mm][0][3]));
                    const uint32_t a2 = pack2(silu_h(cc[mm][1][0]), silu_h(cc[mm][1][1]));
                    const uint32_t a3 = pack2(silu_h(cc[mm][1][2]), silu_h(cc[mm][1][3]));
                    mma16(acc[2 * j + mm], a0, a1, a2, a3, ss0, ss1);
                }
            };
            top();
            stageA(0, c[0]);
#pragma unroll 1
            for (;;) {
                ss0 = movm(q0);
                ss1 = movm(q1);
                last = tb >= hi;
                stageA(1, c[1]); stageB(0, c[0]);
                stageA(2, c[0]); stageB(1, c[1]);
                stageA(3, c[1]); stageB(2, c[0]);
                top();
                stageA(0, c[0]);
                stageB(3, c[1]);
                if (last) break;
            }
#pragma unroll
            for (int j = 0; j < 4; j++)
                stsm4t((fa ^ ((j & 1) << 6)) + (j >> 1) * fs, pack2(acc[2 * j][0], acc[2 * j][1]), pack2(acc[2 * j][2], acc[2 * j][3]),
                       pack2(acc[2 * j + 1][0], acc[2 * j + 1][1]), pack2(acc[2 * j + 1][2], acc[2 * j + 1][3]));
            lo = hi;
            if (lo < e) {
                cp_wait<0>();
                __syncwarp();
                fidx(lo & ~15);
                first_fetch();
            }
        }
    }
    if (warp >= 8) {
        const int tb = tid - 256;
        const int r1 = (warp - 8) * 2 + (lane >> 4);
        const unsigned hl = lane & 15;
        const int s1 = range_start(r1, T) * 16;
        const int e1 = min(range_start(r1 + 1, T) * 16, M);
        const int nl = lds32(sb + SM_LIST + max(e1 - 1, 0) * 4) >> 23;
        const int o1 = ms->off[nl + 1];
        const bool fx = s1 < e1 && ms->off[nl] >= s1 && o1 > e1;
        const bool slow = ms->anyovf;
        bar_sync<0, 512>();
        if (tb == 0) TSTAMP(21);
        if (fx) {
            uint4 u = lds128(sb + SM_RING + r1 * SLOT + 4864 + hl * 16);
            float v[8];
            v[0] = __uint_as_float(u.x << 16); v[1] = __uint_as_float(u.x & 0xffff0000u);
            v[2] = __uint_as_float(u.y << 16); v[3] = __uint_as_float(u.y & 0xffff0000u);
            v[4] = __uint_as_float(u.z << 16); v[5] = __uint_as_float(u.z & 0xffff0000u);
            v[6] = __uint_as_float(u.w << 16); v[7] = __uint_as_float(u.w & 0xffff0000u);
            int s2 = e1;
            for (int r2 = r1 + 1; s2 < o1; r2++) {
                const int e2 = range_start(r2 + 1, T) * 16;
                if (s2 < e2) {
                    u = lds128(sb + SM_RING + r2 * SLOT + 4608 + hl * 16);
                    v[0] += __uint_as_float(u.x << 16); v[1] += __uint_as_float(u.x & 0xffff0000u);
                    v[2] += __uint_as_float(u.y << 16); v[3] += __uint_as_float(u.y & 0xffff0000u);
                    v[4] += __uint_as_float(u.z << 16); v[5] += __uint_as_float(u.z & 0xffff0000u);
                    v[6] += __uint_as_float(u.w << 16); v[7] += __uint_as_float(u.w & 0xffff0000u);
                }
                s2 = e2;
            }
            *reinterpret_cast<uint4*>(smem + SM_AGG + sw<80>(nl, hl)) =
                make_uint4(pack2(v[0], v[1]), pack2(v[2], v[3]), pack2(v[4], v[5]), pack2(v[6], v[7]));
        }
        if (slow) {
            __threadfence();
            bar_sync<2, 256>();
            float* ext = reinterpret_cast<float*>(smem + SM_EXT);
            for (int i = tb; i < 80 * 128; i += 256) ext[i] = 0.f;
            bar_sync<2, 256>();
            const char* Pb = reinterpret_cast<const char*>(sc->P);
            for (int w = -1; w < NWR; w++) {
                const int cnt = w < 0 ? ms->total - CAP : ms->wovf[w];
                for (int k = warp - 8; k < cnt; k += 8) {
                    uint2 en;
                    const uint2* ep = w < 0 ? sc->spill + cta * NSPILL + k : sc->ovf + w * EPC + k;
                    asm volatile("ld.relaxed.gpu.global.v2.u32 {%0,%1}, [%2];" : "=r"(en.x), "=r"(en.y) : "l"(ep) : "memory");
                    const int nl = (int)en.x - node0;
                    const uint32_t eid = en.y;
                    if (nl < 0 || nl >= NPC) continue;
                    const uint32_t sn = src[eid];
                    for (int u = 0; u < 4; u++) {
                        const int f = lane * 4 + u;
                        float h = 0.f;
                        for (int kk = 0; kk < 16; kk++)
                            h = fmaf(__bfloat162float(e_attr[(size_t)eid * 16 + kk]), __bfloat162float(w_msg[(256 + kk) * 128 + f]), h);
                        h = 0.5f * h + __bfloat162float(*reinterpret_cast<const __nv_bfloat16*>(Pb + sn * 256 + f * 2)) +
                            __bfloat162float(*reinterpret_cast<const __nv_bfloat16*>(smem + SM_Q + sw<80>(nl, f >> 3) + (f & 7) * 2));
                        atomicAdd(&ext[nl * 128 + f], __bfloat162float(__float2bfloat16_rn(silu_h(h))));
                    }
                }
            }
            bar_sync<2, 256>();
            for (int i = tb; i < 80 * 128; i += 256) {
                const int r = i >> 7, f = i & 127;
                __nv_bfloat16* pp = reinterpret_cast<__nv_bfloat16*>(smem + SM_AGG + sw<80>(r, f >> 3) + (f & 7) * 2);
                *pp = __float2bfloat16_rn(__bfloat162float(*pp) + ext[i]);
            }
        }
        fence_async();
        bar_arrive<4, 512>();
        return;
    }
    {
        const int wg = warp >> 2;
        float a0[40];
        bar_arrive<0, 512>();
        fence_async();
#pragma unroll
        for (int j = 0; j < 10; j++) {
            const float4 v = *reinterpret_cast<const float4*>(smem + r_off(j) + tid * 16);
            a0[4 * j] = v.x; a0[4 * j + 1] = v.y; a0[4 * j + 2] = v.z; a0[4 * j + 3] = v.w;
        }
        mbar_wait(smem_u32(ms->mbar) + 16);
        bar_sync<4, 512>();
        if (tid == 0) TSTAMP(14);
        asm volatile("" : ACC40(a0)::"memory");
        wgmma_issue_split(a0, sb + SM_WU + wg * 32768 + 16384, sb + SM_AGG);
        auto emit = [&](int j0, int j1, const CUtensorMap* tm) {
#pragma unroll
            for (int j = j0; j < j1; j += 2) {
                uint32_t r[4];
#pragma unroll
                for (int k = 0; k < 4; k++) r[k] = pack2(silu_h(0.5f * a0[4 * j + 2 * k]), silu_h(0.5f * a0[4 * j + 2 * k + 1]));
                stsm4t(sb + SM_OUT + tile_a + j * 1024, r[0], r[1], r[2], r[3]);
            }
            fence_async();
            if (wg == 0) bar_sync<1, 128>(); else bar_sync<3, 128>();
            if ((tid & 127) == 0) {
                tma_store(tm, sb + SM_OUT + wg * 10240 + j0 * 1024, wg * 64, node0 + j0 * 8);
                asm volatile("cp.async.bulk.commit_group;" ::: "memory");
            }
        };
        asm volatile("wgmma.wait_group.sync.aligned 1;" : ACC8(a0, 0), ACC8(a0, 8), ACC8(a0, 16)::"memory");
        if (tid == 0) TSTAMP(26);
        emit(0, 6, &tm_out);
        asm volatile("wgmma.wait_group.sync.aligned 0;" : ACC8(a0, 24), ACC8(a0, 32)::"memory");
        emit(6, 10, &tm_out2);
        if ((tid & 127) == 0) asm volatile("cp.async.bulk.wait_group.read 0;" ::: "memory");
    }
    if (tid == 0) TSTAMP(12);
}

}

typedef CUresult (*EncodeFn)(CUtensorMap*, CUtensorMapDataType, cuuint32_t, void*, const cuuint64_t*, const cuuint64_t*,
                             const cuuint32_t*, const cuuint32_t*, CUtensorMapInterleave, CUtensorMapSwizzle,
                             CUtensorMapL2promotion, CUtensorMapFloatOOBfill);

static void make_map(EncodeFn enc, CUtensorMap* tm, const void* base, int rows, int box_rows) {
    const cuuint64_t dims[2] = {128, (cuuint64_t)rows};
    const cuuint64_t strides[1] = {256};
    const cuuint32_t box[2] = {64, (cuuint32_t)box_rows};
    const cuuint32_t estr[2] = {1, 1};
    enc(tm, CU_TENSOR_MAP_DATA_TYPE_BFLOAT16, 2, const_cast<void*>(base), dims, strides, box, estr, CU_TENSOR_MAP_INTERLEAVE_NONE,
        CU_TENSOR_MAP_SWIZZLE_128B, CU_TENSOR_MAP_L2_PROMOTION_NONE, CU_TENSOR_MAP_FLOAT_OOB_FILL_NONE);
}

extern "C" void kernel_launch(void* const* d_in, const int* in_sizes, int n_in, void* d_out, int out_size) {
    const __nv_bfloat16* x = (const __nv_bfloat16*)d_in[0];
    const __nv_bfloat16* e_attr = (const __nv_bfloat16*)d_in[1];
    const int* src = (const int*)d_in[2];
    const int* dst = (const int*)d_in[3];
    const __nv_bfloat16* w_msg = (const __nv_bfloat16*)d_in[4];

    static int fused = -1;
    static Scratch* sc = nullptr;
    static EncodeFn enc = nullptr;
    if (fused < 0) {
        cudaFuncSetAttribute(mpnn_kernel<1>, cudaFuncAttributeMaxDynamicSharedMemorySize, SM_ALLOC);
        cudaFuncSetAttribute(mpnn_kernel<2>, cudaFuncAttributeMaxDynamicSharedMemorySize, SM_ALLOC);
        cudaFuncSetAttribute(mpnn_kernel<3>, cudaFuncAttributeMaxDynamicSharedMemorySize, SM_ALLOC);
        int dev = 0, sms = 0, occ = 0;
        cudaGetDevice(&dev);
        cudaDeviceGetAttribute(&sms, cudaDevAttrMultiProcessorCount, dev);
        cudaOccupancyMaxActiveBlocksPerMultiprocessor(&occ, mpnn_kernel<3>, THREADS, SM_ALLOC);
        cudaGetSymbolAddress((void**)&sc, g_sc);
        cudaDriverEntryPointQueryResult qr;
        cudaGetDriverEntryPoint("cuTensorMapEncodeTiled", (void**)&enc, cudaEnableDefault, &qr);
        fused = (sms * occ >= NCTA) ? 1 : 0;
    }
    CUtensorMap tm_wm, tm_wu, tm_mail, tm_p, tm_out, tm_out2;
    make_map(enc, &tm_out, d_out, NN, 48);
    make_map(enc, &tm_out2, d_out, NN, NPC - 48);
    make_map(enc, &tm_p, sc->P, NN, NPC);
    {
        const cuuint64_t dims[2] = {RCHUNK * 4, NCTA};
        const cuuint64_t strides[1] = {RCHUNK * 16};
        const cuuint32_t box[2] = {32, NCTA};
        const cuuint32_t estr[2] = {1, 1};
        enc(&tm_mail, CU_TENSOR_MAP_DATA_TYPE_UINT32, 2, sc->mail, dims, strides, box, estr, CU_TENSOR_MAP_INTERLEAVE_NONE,
            CU_TENSOR_MAP_SWIZZLE_NONE, CU_TENSOR_MAP_L2_PROMOTION_NONE, CU_TENSOR_MAP_FLOAT_OOB_FILL_NONE);
    }
    make_map(enc, &tm_wm, d_in[4], 272, 128);
    make_map(enc, &tm_wu, d_in[5], 256, 128);
    if (fused) {
        mpnn_kernel<3><<<NCTA, THREADS, SM_ALLOC, cudaStreamPerThread>>>(x, e_attr, src, dst, w_msg, sc, tm_wm, tm_wu, tm_mail, tm_p, tm_out, tm_out2);
    } else {
        mpnn_kernel<1><<<NCTA, THREADS, SM_ALLOC, cudaStreamPerThread>>>(x, e_attr, src, dst, w_msg, sc, tm_wm, tm_wu, tm_mail, tm_p, tm_out, tm_out2);
        mpnn_kernel<2><<<NCTA, THREADS, SM_ALLOC, cudaStreamPerThread>>>(x, e_attr, src, dst, w_msg, sc, tm_wm, tm_wu, tm_mail, tm_p, tm_out, tm_out2);
    }
}
```

```cpp
#include <cuda_runtime.h>
#include <cuda.h>
#include <cuda_bf16.h>
#include <stdint.h>
#include <stddef.h>

namespace {

constexpr int NN = 10000;
constexpr int EE = 160000;
constexpr int NCTA = 132;
constexpr int NPC = 76;
constexpr int NWR = 125;
constexpr int EPC = 1280;
constexpr int THREADS = 512;
constexpr int MCAP = 31;
constexpr int SCHUNK = NCTA * 8;
constexpr int RCHUNK = 128 * 8;
constexpr int CAP = 2048;
constexpr int NSPILL = NWR * MCAP - CAP;

static_assert(NCTA * NPC >= NN, "nodes");
static_assert(NWR * EPC == EE, "edges");
static_assert(NN <= 16384 && EPC < 2047 && NPC < 80, "entry packing");

constexpr int SLOT = 5120;
constexpr int SM_RING = 0;
constexpr int SM_W12 = 0;
constexpr int SM_WOFF = 65536;
constexpr int SM_W3S = SM_WOFF + 4096;
constexpr int SM_OUT = 0;
constexpr int SM_EXT = 0;
constexpr int SM_AGG = 16 * SLOT;
constexpr int SM_WU = SM_AGG + 20480;
constexpr int SM_X = SM_WU + 65536;
constexpr int SM_ZL = SM_X + 8192;
constexpr int SM_Q = SM_X + 20480;
constexpr int SM_LIST = SM_Q + 20480;
constexpr int LISTB = (CAP + 64) * 4;
constexpr int SM_EID = SM_LIST + LISTB;
constexpr int SM_W3F = SM_EID + LISTB;
constexpr int SM_MISC = SM_W3F + 4096;
constexpr int SM_TRASH = SM_MISC + 2048;
constexpr int SM_TOTAL = SM_TRASH + 256;
constexpr int SM_ALLOC = SM_TOTAL;
static_assert(2 * LISTB >= SCHUNK * 16, "staging");
static_assert(SM_ALLOC <= 232448, "smem");

struct Misc {
    int cnt[NCTA];
    int ncnt[128];
    int off[100];
    int ovf;
    int anyovf;
    int total;
    int pad;
    int wovf[128];
    uint4 pad2;
    unsigned long long mbar[3];
};
constexpr int MISC_ZERO16 = 124;
static_assert(offsetof(Misc, mbar) == MISC_ZERO16 * 16, "misc layout");
static_assert(sizeof(Misc) <= 2048, "misc");

struct Scratch {
    uint4 P[NN * 16];
    uint4 mail[NCTA * RCHUNK];
    uint2 ovf[NWR * EPC];
    uint2 spill[NCTA * NSPILL];
    unsigned sync[64];
};
__device__ Scratch g_sc;

#define TSTAMP(i) do {} while (0)

__device__ __forceinline__ uint32_t smem_u32(const void* p) { return (uint32_t)__cvta_generic_to_shared(p); }

template <int ROWS>
__device__ __forceinline__ uint32_t sw(int row, int chunk) {
    return (uint32_t)((chunk >> 3) * (ROWS * 128) + row * 128 + (((chunk & 7) ^ (row & 7)) << 4));
}

__device__ __forceinline__ uint32_t w3sw(unsigned row, unsigned chunk) {
    return (chunk >> 3) * 2048 + row * 128 + (((chunk & 7) ^ ((row & 1) | ((row >> 1) & 6))) << 4);
}
__device__ __forceinline__ constexpr int r_off(int j) {
    return j < 4 ? SM_WU + j * 4096 : j < 8 ? SM_WU + 32768 + (j - 4) * 4096 : SM_X + (j - 8) * 4096;
}
__device__ __forceinline__ void cp16(uint32_t dst, const void* src) {
    asm volatile("cp.async.cg.shared.global [%0], [%1], 16;" ::"r"(dst), "l"(src) : "memory");
}
template <int SCALE, int OFF>
__device__ __forceinline__ void cp16g(uint32_t dst, const void* base, uint32_t idx, int skip) {
    asm volatile("{.reg .pred p; .reg .b64 a; mad.wide.u32 a, %2, %4, %1; setp.eq.s32 p, %3, 0;\n"
                 "@p cp.async.cg.shared.global [%0], [a+%5], 16;}"
                 ::"r"(dst), "l"(base), "r"(idx), "r"(skip), "n"(SCALE), "n"(OFF) : "memory");
}
__device__ __forceinline__ void cp_commit() { asm volatile("cp.async.commit_group;" ::: "memory"); }
template <int N>
__device__ __forceinline__ void cp_wait() { asm volatile("cp.async.wait_group %0;" ::"n"(N) : "memory"); }
template <int ID, int N>
__device__ __forceinline__ void bar_sync() { asm volatile("bar.sync %0, %1;" ::"n"(ID), "n"(N) : "memory"); }
template <int ID, int N>
__device__ __forceinline__ void bar_arrive() { asm volatile("bar.arrive %0, %1;" ::"n"(ID), "n"(N) : "memory"); }
__device__ __forceinline__ void fence_async() { asm volatile("fence.proxy.async.shared::cta;" ::: "memory"); }

__device__ __forceinline__ void ldsm4t(uint32_t (&r)[4], uint32_t a) {
    asm volatile("ldmatrix.sync.aligned.m8n8.x4.trans.shared.b16 {%0,%1,%2,%3}, [%4];"
                 : "=r"(r[0]), "=r"(r[1]), "=r"(r[2]), "=r"(r[3]) : "r"(a));
}
__device__ __forceinline__ uint4 lds128(uint32_t a) {
    uint4 v;
    asm volatile("ld.shared.v4.u32 {%0,%1,%2,%3}, [%4];" : "=r"(v.x), "=r"(v.y), "=r"(v.z), "=r"(v.w) : "r"(a));
    return v;
}
__device__ __forceinline__ uint2 lds64(uint32_t a) {
    uint2 v;
    asm volatile("ld.shared.v2.u32 {%0,%1}, [%2];" : "=r"(v.x), "=r"(v.y) : "r"(a));
    return v;
}
__device__ __forceinline__ uint32_t lds32(uint32_t a) {
    uint32_t v;
    asm volatile("ld.shared.u32 %0, [%1];" : "=r"(v) : "r"(a));
    return v;
}
__device__ __forceinline__ uint32_t lds16(uint32_t a) {
    uint32_t v;
    asm volatile("ld.shared.u16 %0, [%1];" : "=r"(v) : "r"(a));
    return v;
}
__device__ __forceinline__ void sts32(uint32_t a, uint32_t v) {
    asm volatile("st.shared.u32 [%0], %1;" ::"r"(a), "r"(v) : "memory");
}
__device__ __forceinline__ void stsm4t(uint32_t a, uint32_t r0, uint32_t r1, uint32_t r2, uint32_t r3) {
    asm volatile("stmatrix.sync.aligned.m8n8.x4.trans.shared.b16 [%0], {%1,%2,%3,%4};"
                 ::"r"(a), "r"(r0), "r"(r1), "r"(r2), "r"(r3) : "memory");
}
__device__ __forceinline__ void mma16(float (&d)[4], const uint32_t a0, const uint32_t a1, const uint32_t a2,
                                      const uint32_t a3, const uint32_t b0, const uint32_t b1) {
    asm("mma.sync.aligned.m16n8k16.row.col.f32.bf16.bf16.f32 {%0,%1,%2,%3}, {%4,%5,%6,%7}, {%8,%9}, {%0,%1,%2,%3};"
        : "+f"(d[0]), "+f"(d[1]), "+f"(d[2]), "+f"(d[3])
        : "r"(a0), "r"(a1), "r"(a2), "r"(a3), "r"(b0), "r"(b1));
}
__device__ __forceinline__ void mma8(float (&d)[4], const uint32_t a0, const uint32_t a1, const uint32_t b0) {
    asm("mma.sync.aligned.m16n8k8.row.col.f32.bf16.bf16.f32 {%0,%1,%2,%3}, {%4,%5}, {%6}, {%0,%1,%2,%3};"
        : "+f"(d[0]), "+f"(d[1]), "+f"(d[2]), "+f"(d[3])
        : "r"(a0), "r"(a1), "r"(b0));
}
__device__ __forceinline__ uint32_t movm(uint32_t a) {
    uint32_t d;
    asm("movmatrix.sync.aligned.m8n8.trans.b16 %0, %1;" : "=r"(d) : "r"(a));
    return d;
}
__device__ __forceinline__ void ldsm4tf(float (&r)[4], uint32_t a) {
    asm volatile("ldmatrix.sync.aligned.m8n8.x4.trans.shared.b16 {%0,%1,%2,%3}, [%4];"
                 : "=f"(r[0]), "=f"(r[1]), "=f"(r[2]), "=f"(r[3]) : "r"(a));
}
__device__ __forceinline__ int range_start(int r, int T) {
    const int t0 = ((r >> 2) * T) >> 2, n = ((((r >> 2) + 1) * T) >> 2) - t0, b = r & 3;
    return t0 + b * (n >> 2) + min(b, n & 3);
}
__device__ __forceinline__ uint32_t pack2(float lo, float hi) {
    uint32_t r;
    asm("cvt.rn.bf16x2.f32 %0, %1, %2;" : "=r"(r) : "f"(hi), "f"(lo));
    return r;
}
__device__ __forceinline__ uint32_t half2x(uint32_t a) {
    uint32_t r;
    asm("mul.rn.bf16x2 %0, %1, %2;" : "=r"(r) : "r"(a), "r"(0x3F003F00u));
    return r;
}
__device__ __forceinline__ float tanh_fast(float x) {
    float t;
    asm("tanh.approx.f32 %0, %1;" : "=f"(t) : "f"(x));
    return t;
}
__device__ __forceinline__ float silu_h(float h) { return fmaf(h, tanh_fast(h), h); }

__device__ __forceinline__ unsigned ld_relaxed32(const void* p) {
    unsigned v;
    asm volatile("ld.relaxed.gpu.global.u32 %0, [%1];" : "=r"(v) : "l"(p) : "memory");
    return v;
}
__device__ __forceinline__ unsigned ld_poll32(const void* p) {
    unsigned v;
    asm volatile("ld.acquire.gpu.global.u32 %0, [%1];" : "=r"(v) : "l"(p) : "memory");
    return v;
}
__device__ __forceinline__ uint32_t atoms_inc(uint32_t addr) {
    uint32_t r;
    asm volatile("atom.shared.add.u32 %0, [%1], 1;" : "=r"(r) : "r"(addr) : "memory");
    return r;
}
__device__ __forceinline__ void tma2d(uint32_t dst, const CUtensorMap* tm, int c0, int c1, uint32_t bar) {
    asm volatile("cp.async.bulk.tensor.2d.shared::cluster.global.mbarrier::complete_tx::bytes [%0], [%1, {%3, %4}], [%2];"
                 ::"r"(dst), "l"(tm), "r"(bar), "r"(c0), "r"(c1) : "memory");
}
__device__ __forceinline__ void tma_w(uint32_t dst, const CUtensorMap* tm, int row, uint32_t bar) {
    asm volatile("mbarrier.arrive.expect_tx.shared.b64 _, [%0], %1;" ::"r"(bar), "n"(32768) : "memory");
    tma2d(dst, tm, 0, row, bar);
    tma2d(dst + 32768, tm, 64, row, bar);
}
__device__ __forceinline__ void tma_store(const CUtensorMap* tm, uint32_t src, int c0, int c1) {
    asm volatile("cp.async.bulk.tensor.2d.global.shared::cta.bulk_group [%0, {%2, %3}], [%1];"
                 ::"l"(tm), "r"(src), "r"(c0), "r"(c1) : "memory");
}
__device__ __forceinline__ void mbar_wait(uint32_t bar) {
    uint32_t ok;
    int sp = 0;
    do {
        asm volatile("{.reg .pred p; mbarrier.try_wait.parity.shared.b64 p, [%1], 0; selp.u32 %0, 1, 0, p;}" : "=r"(ok) : "r"(bar) : "memory");
    } while (!ok && ++sp < (1 << 22));
}
template <int N>
__device__ __forceinline__ void cp_rows(uint32_t dst, const void* src) {
#pragma unroll
    for (int i = 0; i < N; i++)
        asm volatile("cp.async.cg.shared.global [%0], [%1], 16;" ::"r"(dst + i * 2048), "l"((const char*)src + i * 4096) : "memory");
}

#define ACC40(d)                                                                                              \
    "+f"(d[0]), "+f"(d[1]), "+f"(d[2]), "+f"(d[3]), "+f"(d[4]), "+f"(d[5]), "+f"(d[6]), "+f"(d[7]),         \
    "+f"(d[8]), "+f"(d[9]), "+f"(d[10]), "+f"(d[11]), "+f"(d[12]), "+f"(d[13]), "+f"(d[14]), "+f"(d[15]),   \
    "+f"(d[16]), "+f"(d[17]), "+f"(d[18]), "+f"(d[19]), "+f"(d[20]), "+f"(d[21]), "+f"(d[22]), "+f"(d[23]), \
    "+f"(d[24]), "+f"(d[25]), "+f"(d[26]), "+f"(d[27]), "+f"(d[28]), "+f"(d[29]), "+f"(d[30]), "+f"(d[31]), \
    "+f"(d[32]), "+f"(d[33]), "+f"(d[34]), "+f"(d[35]), "+f"(d[36]), "+f"(d[37]), "+f"(d[38]), "+f"(d[39])

__device__ __forceinline__ void wgmma_issue(float (&d)[40], uint32_t w_addr, uint32_t t_addr) {
    const uint32_t la = (w_addr >> 4) | 0x10000u, lb = (t_addr >> 4) | 0x10000u;
    asm volatile("wgmma.fence.sync.aligned;" ::: "memory");
#pragma unroll
    for (int ks = 0; ks < 8; ks++) {
        asm volatile(
            "{.reg .b64 da, db; .reg .pred p;\n"
            "setp.ne.s32 p, %43, 0;\n"
            "mov.b64 da, {%40, %42};\n"
            "mov.b64 db, {%41, %42};\n"
            "wgmma.mma_async.sync.aligned.m64n80k16.f32.bf16.bf16 "
            "{%0,%1,%2,%3,%4,%5,%6,%7,%8,%9,%10,%11,%12,%13,%14,%15,%16,%17,%18,%19,"
            "%20,%21,%22,%23,%24,%25,%26,%27,%28,%29,%30,%31,%32,%33,%34,%35,%36,%37,%38,%39},"
            "da, db, p, 1, 1, 1, 0;}"
            : ACC40(d)
            : "r"(la + ks * 128), "r"(lb + (ks >> 2) * 640 + (ks & 3) * 2), "r"(0x40000040u), "r"(ks > 0 ? 1 : 0));
    }
    asm volatile("wgmma.commit_group.sync.aligned;" ::: "memory");
}
#define ACC8(d, b) "+f"(d[b]), "+f"(d[b + 1]), "+f"(d[b + 2]), "+f"(d[b + 3]), "+f"(d[b + 4]), "+f"(d[b + 5]), "+f"(d[b + 6]), "+f"(d[b + 7])
__device__ __forceinline__ void wgmma_issue_split(float (&d)[40], uint32_t w_addr, uint32_t t_addr) {
    const uint32_t la = (w_addr >> 4) | 0x10000u, lb = (t_addr >> 4) | 0x10000u;
    asm volatile("wgmma.fence.sync.aligned;" ::: "memory");
#pragma unroll
    for (int ks = 0; ks < 8; ks++)
        asm volatile(
            "{.reg .b64 da, db;\n"
            "mov.b64 da, {%24, %26};\n"
            "mov.b64 db, {%25, %26};\n"
            "wgmma.mma_async.sync.aligned.m64n48k16.f32.bf16.bf16 "
            "{%0,%1,%2,%3,%4,%5,%6,%7,%8,%9,%10,%11,%12,%13,%14,%15,%16,%17,%18,%19,%20,%21,%22,%23},"
            "da, db, 1, 1, 1, 1, 0;}"
            : ACC8(d, 0), ACC8(d, 8), ACC8(d, 16)
            : "r"(la + ks * 128), "r"(lb + (ks >> 2) * 640 + (ks & 3) * 2), "r"(0x40000040u));
    asm volatile("wgmma.commit_group.sync.aligned;" ::: "memory");
#pragma unroll
    for (int ks = 0; ks < 8; ks++)
        asm volatile(
            "{.reg .b64 da, db;\n"
            "mov.b64 da, {%16, %18};\n"
            "mov.b64 db, {%17, %18};\n"
            "wgmma.mma_async.sync.aligned.m64n32k16.f32.bf16.bf16 "
            "{%0,%1,%2,%3,%4,%5,%6,%7,%8,%9,%10,%11,%12,%13,%14,%15},"
            "da, db, 1, 1, 1, 1, 0;}"
            : ACC8(d, 24), ACC8(d, 32)
            : "r"(la + ks * 128), "r"(lb + 384 + (ks >> 2) * 640 + (ks & 3) * 2), "r"(0x40000040u));
    asm volatile("wgmma.commit_group.sync.aligned;" ::: "memory");
}
template <int N>
__device__ __forceinline__ void wgmma_wait(float (&d)[40]) {
    asm volatile("wgmma.wait_group.sync.aligned %40;" : ACC40(d) : "n"(N) : "memory");
}
template <bool HALF>
__device__ __forceinline__ void store_tile(uint32_t a, const float (&d)[40]) {
#pragma unroll
    for (int j = 0; j < 10; j += 2) {
        uint32_t r[4];
#pragma unroll
        for (int k = 0; k < 4; k++) {
            r[k] = pack2(d[4 * j + 2 * k], d[4 * j + 2 * k + 1]);
            if (HALF) r[k] = half2x(r[k]);
        }
        stsm4t(a + j * 1024, r[0], r[1], r[2], r[3]);
    }
}

template <int MODE>
__global__ void __launch_bounds__(THREADS, 1)
mpnn_kernel(const __nv_bfloat16* __restrict__ x, const __nv_bfloat16* __restrict__ e_attr,
            const int* __restrict__ src, const int* __restrict__ dst,
            const __nv_bfloat16* __restrict__ w_msg,
            Scratch* __restrict__ sc,
            const __grid_constant__ CUtensorMap tm_wm, const __grid_constant__ CUtensorMap tm_wu,
            const __grid_constant__ CUtensorMap tm_mail, const __grid_constant__ CUtensorMap tm_p,
            const __grid_constant__ CUtensorMap tm_out, const __grid_constant__ CUtensorMap tm_out2) {
    extern __shared__ __align__(1024) uint8_t smem[];
    const uint32_t sb = smem_u32(smem);
    Misc* ms = reinterpret_cast<Misc*>(smem + SM_MISC);
    const unsigned tid = threadIdx.x, lane = tid & 31;
    __builtin_assume(tid < THREADS);
    const unsigned cta = blockIdx.x;
    __builtin_assume(cta < NCTA);
    uint32_t dv[5], sv[5];
    if ((MODE & 1) && cta < NWR && tid >= 256) {
        const int* dp = dst + cta * EPC - 256;
        const int* sp = src + cta * EPC - 256;
        asm volatile("ld.global.nc.v4.u32 {%0,%1,%2,%3}, [%4];" : "=r"(dv[0]), "=r"(dv[1]), "=r"(dv[2]), "=r"(dv[3]) : "l"(dp - 768 + tid * 4));
        asm volatile("ld.global.nc.u32 %0, [%1];" : "=r"(dv[4]) : "l"(dp + 1024 + tid));
        asm volatile("ld.global.nc.v4.u32 {%0,%1,%2,%3}, [%4];" : "=r"(sv[0]), "=r"(sv[1]), "=r"(sv[2]), "=r"(sv[3]) : "l"(sp - 768 + tid * 4));
        asm volatile("ld.global.nc.u32 %0, [%1];" : "=r"(sv[4]) : "l"(sp + 1024 + tid));
    }
    const int warp = __shfl_sync(0xffffffffu, tid >> 5, 0);
    if (tid == 0) TSTAMP(0);

    const unsigned g = lane >> 2, q = lane & 3;
    const int node0 = cta * NPC;
    const uint32_t tile_a = sw<80>(((lane >> 4) & 1) * 8 + (lane & 7), (warp & 7) * 2 + ((lane >> 3) & 1));

    if (warp >= 8) {
        const unsigned tb = tid - 256;
        __builtin_assume(tb < 256);
        const bool writer = (MODE & 1) && cta < NWR;
        bar_arrive<3, 512>();
        unsigned htarget = 0;
        if (tb == 0 && MODE == 3) htarget = ld_relaxed32(&sc->sync[32]);
        if (tb == 32) asm volatile("prefetch.tensormap [%0];" ::"l"(&tm_mail) : "memory");
        if (tb < MISC_ZERO16) reinterpret_cast<uint4*>(ms)[tb] = make_uint4(0, 0, 0, 0);
        bar_sync<2, 256>();
        if (tb == 0) TSTAMP(17);
        if (warp == 8) asm volatile("bar.arrive %0, 288;" ::"r"(5 + (writer ? dv[0] >> 30 : 0)) : "memory");
        if (writer) {
            uint32_t own[5], pos[5];
#pragma unroll
            for (int i = 0; i < 5; i++) {
                own[i] = (dv[i] * 55189u) >> 22;
                pos[i] = atoms_inc(sb + SM_MISC + own[i] * 4);
            }
            if (tb == 0) TSTAMP(18);
            uint32_t pmax = 0;
#pragma unroll
            for (int i = 0; i < 5; i++) {
                const uint32_t nl = dv[i] - own[i] * NPC;
                const uint32_t el1 = i < 4 ? tb * 4 + i + 1 : tb + 1025;
                sts32(sb + SM_LIST + own[i] * 128 + (pos[i] < MCAP ? pos[i] * 4 + 4 : 0), (sv[i] * 128u + nl) * 2048u + el1);
                pmax = max(pmax, pos[i]);
            }
            if (pmax >= MCAP) {
#pragma unroll
                for (int i = 0; i < 5; i++) {
                    if (pos[i] >= MCAP) {
                        const int k = atomicAdd(&ms->ovf, 1);
                        sc->ovf[cta * EPC + k] = make_uint2(dv[i], cta * EPC + (i < 4 ? tb * 4 + i : tb + 1024));
                    }
                }
                __threadfence();
            }
            if (tb == 0) TSTAMP(8);
            bar_sync<2, 256>();
            if (tb == 0) TSTAMP(19);
            if (tb < NCTA) sts32(sb + SM_LIST + tb * 128, ((uint32_t)ms->ovf << 11) | (uint32_t)ms->cnt[tb]);
            fence_async();
            bar_sync<2, 256>();
            if (tb == 0) {
                tma_store(&tm_mail, sb + SM_LIST, cta * 32, 0);
                asm volatile("cp.async.bulk.commit_group;" ::: "memory");
                TSTAMP(9);
                asm volatile("cp.async.bulk.wait_group 0;" ::: "memory");
                TSTAMP(23);
            }
        }
        if (!(MODE & 2)) return;
        if (MODE == 3) {
            if (tb == 0) {
                asm volatile("red.release.gpu.global.add.u32 [%0], 1;" ::"l"(&sc->sync[32]) : "memory");
                htarget = htarget - htarget % NCTA + NCTA;
                int sp = 0;
                while ((int)(ld_poll32(&sc->sync[32]) - htarget) < 0 && ++sp < (1 << 22)) {}
                TSTAMP(24);
            }
            bar_sync<2, 256>();
        }
        uint32_t w[2][8];
        {
            const uint4* mine = sc->mail + cta * RCHUNK + (tb >> 2) * 8 + (tb & 3);
            const uint4* mine2 = tb + 256 < NWR * 4 ? mine + 512 : mine;
            asm volatile("ld.relaxed.gpu.global.v4.u32 {%0,%1,%2,%3}, [%16];\n"
                         "ld.relaxed.gpu.global.v4.u32 {%8,%9,%10,%11}, [%17];\n"
                         "ld.relaxed.gpu.global.v4.u32 {%4,%5,%6,%7}, [%16+64];\n"
                         "ld.relaxed.gpu.global.v4.u32 {%12,%13,%14,%15}, [%17+64];"
                         : "=r"(w[0][0]), "=r"(w[0][1]), "=r"(w[0][2]), "=r"(w[0][3]), "=r"(w[0][4]), "=r"(w[0][5]), "=r"(w[0][6]), "=r"(w[0][7]),
                           "=r"(w[1][0]), "=r"(w[1][1]), "=r"(w[1][2]), "=r"(w[1][3]), "=r"(w[1][4]), "=r"(w[1][5]), "=r"(w[1][6]), "=r"(w[1][7])
                         : "l"(mine), "l"(mine2) : "memory");
        }
        uint32_t hd[2];
        hd[0] = __shfl_sync(0xffffffffu, w[0][0], lane & ~3u);
        hd[1] = __shfl_sync(0xffffffffu, w[1][0], lane & ~3u);
        if (tb + 256 >= NWR * 4) hd[1] = 0;
        if (tb == 0) TSTAMP(10);
        int lim[2];
#pragma unroll
        for (int b = 0; b < 2; b++) {
            if ((hd[b] & 0x7ffu) > MCAP) { ms->wovf[(tb >> 2) + 64 * b] = hd[b] >> 11; ms->anyovf = 1; }
            lim[b] = (int)(hd[b] & 0x7ffu) - (int)(tb & 3) * 4;
        }
        const bool second = __any_sync(0xffffffffu, max(lim[0], lim[1]) >= 16);
        const uint32_t dummy = (96u + lane) << 11;
        if ((tb & 3) == 0) w[0][0] = w[1][0] = dummy;
        uint32_t rk[2][8];
        const uint32_t nc = smem_u32(ms->ncnt);
        auto hist = [&](int i0) {
#pragma unroll
            for (int b = 0; b < 2; b++)
#pragma unroll
                for (int i = i0; i < i0 + 4; i++) {
                    w[b][i] = lim[b] >= (i & 3) + (i >> 2) * 16 ? w[b][i] : dummy;
                    rk[b][i] = atoms_inc(nc + ((w[b][i] >> 9) & 0x1fc));
                }
        };
        hist(0);
        if (second) hist(4);
        const uint32_t wo = sb + SM_WOFF + (warp - 8) * 512;
        sts32(wo + 384 + lane * 4, 1u << 20);
        if (tb == 0) TSTAMP(20);
        bar_sync<2, 256>();
        int total;
        {
            const int c0 = lds32(nc + lane * 12), c1 = lds32(nc + lane * 12 + 4), c2 = lds32(nc + lane * 12 + 8);
            int s = c0 + c1 + c2;
#pragma unroll
            for (int d = 1; d < 32; d <<= 1) {
                const int t = __shfl_up_sync(0xffffffffu, s, d);
                if (lane >= d) s += t;
            }
            sts32(wo + lane * 12, s - c2 - c1 - c0);
            sts32(wo + lane * 12 + 4, s - c2 - c1);
            sts32(wo + lane * 12 + 8, s - c2);
            total = __shfl_sync(0xffffffffu, s, 31);
            if (warp == 15) {
                ms->off[lane * 3] = min(s - c2 - c1 - c0, CAP);
                ms->off[lane * 3 + 1] = min(s - c2 - c1, CAP);
                ms->off[lane * 3 + 2] = min(s - c2, CAP);
                if (lane == 31) { ms->off[96] = min(s, CAP); ms->total = s; if (s > CAP) ms->anyovf = 1; }
                if (total < CAP) {
                    const uint32_t pa = sb + SM_LIST + (total + lane) * 4;
                    sts32(pa, 79u << 23);
                    sts32(pa + LISTB, 0u);
                    if (lane < 16) sts32(pa + 128, 79u << 23);
                }
            }
            __syncwarp();
        }
        if (tb == 0) TSTAMP(22);
        const uint32_t eb = (tb >> 2) * EPC - 1;
        auto scatter = [&](int i0) {
#pragma unroll
            for (int b = 0; b < 2; b++)
#pragma unroll
                for (int i = i0; i < i0 + 4; i++) rk[b][i] += lds32(wo + ((w[b][i] >> 9) & 0x1fc));
#pragma unroll
            for (int b = 0; b < 2; b++)
#pragma unroll
                for (int i = i0; i < i0 + 4; i++) {
                    const uint32_t a = sb + SM_LIST + min(rk[b][i], (uint32_t)(CAP + 63)) * 4;
                    sts32(a, (w[b][i] >> 18) | ((w[b][i] << 12) & 0x3f800000u));
                    sts32(a + LISTB, eb + b * (64 * EPC) + (w[b][i] & 0x7ff));
                }
            if (total > CAP) {
#pragma unroll
                for (int b = 0; b < 2; b++)
#pragma unroll
                    for (int i = i0; i < i0 + 4; i++)
                        if (rk[b][i] >= CAP && rk[b][i] < (1u << 20))
                            sc->spill[cta * NSPILL + rk[b][i] - CAP] = make_uint2(node0 + ((w[b][i] >> 11) & 127), eb + b * (64 * EPC) + (w[b][i] & 0x7ff));
            }
        };
        scatter(0);
        if (second) scatter(4);
        if (tb == 0) TSTAMP(11);
    } else {
        unsigned target = 0;
        const uint32_t mb = smem_u32(ms->mbar);
        {
            const unsigned r0 = tid >> 4, c0 = tid & 15;
            bar_sync<3, 512>();
            cp_rows<8>(sb + SM_W12 + sw<256>(r0, c0), reinterpret_cast<const uint4*>(w_msg) + tid);
            cp16(sb + SM_W3S + w3sw(r0, c0), reinterpret_cast<const uint4*>(w_msg) + 4096 + tid);
            const uint32_t dx = sb + SM_X + sw<80>(r0, c0);
            const uint4* xg = reinterpret_cast<const uint4*>(x) + c0;
            if (tid == 32 && MODE == 3) target = ld_relaxed32(&sc->sync[0]);
            if (tid == 160) asm volatile("prefetch.tensormap [%0];" ::"l"(&tm_p) : "memory");
            if (tid == 64) asm volatile("prefetch.tensormap [%0];" ::"l"(&tm_wu) : "memory");
            if (tid == 96) asm volatile("prefetch.tensormap [%0];" ::"l"(&tm_out) : "memory");
            if (tid == 128) asm volatile("prefetch.tensormap [%0];" ::"l"(&tm_out2) : "memory");
            if (tid == 0) {
                asm volatile("mbarrier.init.shared.b64 [%0], 1;" ::"r"(mb) : "memory");
                asm volatile("mbarrier.init.shared.b64 [%0], 1;" ::"r"(mb + 8) : "memory");
                asm volatile("mbarrier.init.shared.b64 [%0], 1;" ::"r"(mb + 16) : "memory");
                asm volatile("fence.mbarrier_init.release.cluster;" ::: "memory");
                if (MODE & 2) {
                    tma_w(sb + SM_W12 + 16384, &tm_wm, 128, mb);
                    tma_w(sb + SM_WU, &tm_wu, 0, mb + 8);
                }
            }
#pragma unroll
            for (int i = 0; i < 2; i++) cp16(dx + i * 2048, xg + min(node0 + r0 + i * 16, (unsigned)(NN - 1)) * 16);
            bar_sync<5, 288>();
#pragma unroll
            for (int i = 2; i < 5; i++) cp16(dx + i * 2048, xg + min(node0 + r0 + i * 16, (unsigned)(NN - 1)) * 16);
            cp_commit();
        }
        const int wg = warp >> 2;
        float a0[40];
        cp_wait<0>();
        fence_async();
        target = target - target % NCTA + NCTA;
        if (tid == 32) sts32(sb + SM_TRASH, target);
        bar_sync<1, 256>();
        if (tid == 0) TSTAMP(1);
        if (MODE & 1) {
            wgmma_issue(a0, sb + SM_W12 + wg * 32768, sb + SM_X);
            wgmma_wait<0>(a0);
            if (tid == 0) TSTAMP(15);
            store_tile<true>(sb + SM_AGG + tile_a, a0);
            fence_async();
            bar_sync<1, 256>();
            if (tid == 0) TSTAMP(16);
            if (tid == 0) {
                tma_store(&tm_p, sb + SM_AGG, 0, node0);
                tma_store(&tm_p, sb + SM_AGG + 10240, 64, node0);
                asm volatile("cp.async.bulk.commit_group;" ::: "memory");
            }
        }
        if (!(MODE & 2)) {
            asm volatile("cp.async.bulk.wait_group 0;" ::: "memory");
            return;
        }
        float a1[40];
        mbar_wait(mb);
        wgmma_issue(a0, sb + SM_W12 + wg * 32768 + 16384, sb + SM_X);
        mbar_wait(mb + 8);
        wgmma_issue(a1, sb + SM_WU + wg * 32768, sb + SM_X);
        wgmma_wait<0>(a0);
        asm volatile("" : ACC40(a1)::"memory");
        bar_sync<1, 256>();
        if (tid == 0) {
            if (MODE == 3) {
                TSTAMP(4);
                asm volatile("cp.async.bulk.wait_group 0;" ::: "memory");
                TSTAMP(2);
                asm volatile("red.release.gpu.global.add.u32 [%0], 1;" ::"l"(&sc->sync[0]) : "memory");
                TSTAMP(3);
            }
            if (cta < NWR)
                asm volatile("cp.async.bulk.prefetch.L2.global [%0], %1;"
                             ::"l"(reinterpret_cast<const char*>(e_attr) + (size_t)cta * (EPC * 32)), "n"(EPC * 32) : "memory");
        }
        store_tile<false>(sb + SM_Q + tile_a, a0);
        {
            uint32_t f[4];
            const unsigned r = lane & 7, mat = lane >> 3;
            ldsm4t(f, sb + SM_W3S + w3sw(4 * (r >> 1) + (r & 1) + 2 * (mat >> 1), warp * 2 + (mat & 1)));
            reinterpret_cast<uint4*>(smem + SM_W3F)[tid] = make_uint4(half2x(f[0]), half2x(f[1]), half2x(f[2]), half2x(f[3]));
        }
#pragma unroll
        for (int j = 0; j < 10; j++)
            *reinterpret_cast<float4*>(smem + r_off(j) + tid * 16) =
                make_float4(0.5f * a1[4 * j], 0.5f * a1[4 * j + 1], 0.5f * a1[4 * j + 2], 0.5f * a1[4 * j + 3]);
        if (tid >= 224) *reinterpret_cast<uint4*>(smem + SM_ZL + (lane >> 3) * 1024 + (lane & 7) * 16) = make_uint4(0, 0, 0, 0);
        if (tid == 0) TSTAMP(25);
        if (tid == 32 && MODE == 3) {
            TSTAMP(7);
            int sp = 0;
            while ((int)(ld_poll32(&sc->sync[0]) - target) < 0 && ++sp < (1 << 22)) {}
            TSTAMP(5);
        }
    }
    bar_sync<0, 512>();
    if (tid == 0) TSTAMP(6);

    const int M = ms->off[96];
    const int T = (M + 15) >> 4;
    const int rg = (warp & 3) * 4 + (warp >> 2);
    const int s = range_start(rg, T) * 16;
    const int e = min(range_start(rg + 1, T) * 16, M);
    const uint32_t ring = sb + SM_RING + rg * SLOT;
    {
        const unsigned fr = lane >> 3, fc = lane & 7;
        const char* Pb0 = reinterpret_cast<const char*>(sc->P) + ((fc ^ fr) << 4);
        const char* Pb1 = reinterpret_cast<const char*>(sc->P) + ((fc ^ fr ^ 4) << 4);
        const char* Eb = reinterpret_cast<const char*>(e_attr) + (lane & 1) * 16;
        asm volatile("" : "+l"(Pb0), "+l"(Pb1), "+l"(Eb));
        const uint32_t fdst = ring + lane * 16;
        const unsigned ledge = (lane & 6) | ((lane ^ (lane >> 3) ^ 1) & 1);
        const uint32_t lz = ((lane & 1) ? ring + ledge * 128 : sb + SM_ZL) + (((lane >> 4) ^ ledge) << 4);
        const uint32_t w3a = sb + SM_W3F + lane * 16;
        uint32_t sn[4], ei;
        auto fidx = [&](int tb) {
#pragma unroll
            for (int i = 0; i < 4; i++) sn[i] = lds16(sb + SM_LIST + (tb + fr) * 4 + i * 16);
            ei = lds32(sb + SM_EID + (tb + (lane >> 1)) * 4);
        };
        auto fetchP = [&](int h, int skip) {
#pragma unroll
            for (int i = 0; i < 4; i++) {
                if (h == 0) cp16g<256, 0>(fdst + i * 512, (i & 1) ? Pb1 : Pb0, sn[i], skip);
                else cp16g<256, 128>(fdst + 2048 + i * 512, (i & 1) ? Pb1 : Pb0, sn[i], skip);
            }
        };
        auto fetchE = [&](int skip) { cp16g<32, 0>(fdst + 4096, Eb, ei, skip); };
        int lo = s;
        auto first_fetch = [&]() {
            const int skip = lo >= e;
            fetchE(skip);
            fetchP(0, skip);
            cp_commit();
            fetchP(1, skip);
            cp_commit();
        };
        fidx(lo);
        if (warp >= 4) asm volatile("bar.sync %0, 256;" ::"r"(4 + (warp >> 2)) : "memory");
        fetchE(lo >= e);
        fetchP(0, lo >= e);
        cp_commit();
        if (warp < 12) asm volatile("bar.arrive %0, 256;" ::"r"(5 + (warp >> 2)) : "memory");
        fetchP(1, lo >= e);
        cp_commit();
        if (tid == 480) tma_w(sb + SM_WU + 16384, &tm_wu, 128, smem_u32(ms->mbar) + 16);
        {
            const int nd = warp * 5 + min(lane, 4u);
            unsigned em = __ballot_sync(0xffffffffu, ms->off[nd] == ms->off[nd + 1]) & 31u;
            while (em) {
                const int k = __ffs(em) - 1;
                em &= em - 1;
                *reinterpret_cast<uint2*>(smem + SM_AGG + sw<80>(warp * 5 + k, lane >> 1) + (lane & 1) * 8) = make_uint2(0, 0);
            }
        }
        if (lane == 0) {
            uint32_t desc = 0;
            if (s < e) {
                const int nl = lds32(sb + SM_LIST + (e - 1) * 4) >> 23;
                const int o1 = ms->off[nl + 1];
                if (ms->off[nl] >= s && o1 > e) {
                    desc = nl;
                    int s2 = e;
                    for (int r2 = rg + 1; s2 < o1; r2++) {
                        const int e2 = range_start(r2 + 1, T) * 16;
                        if (s2 < e2) desc |= 256u << r2;
                        s2 = e2;
                    }
                }
            }
            ms->cnt[rg] = desc;
        }
        while (lo < e) {
            int tb = lo & ~15;
            const int nb = lds32(sb + SM_LIST + lo * 4) >> 23;
            const int hi = min(e, ms->off[min(nb + 8, 96)]);
            const int o0 = ms->off[nb + 2 * q];
            const uint32_t cn0 = ms->off[nb + 2 * q + 1] - o0;
            const uint32_t cn1 = ms->off[nb + 2 * q + 2] - o0 - cn0;
            uint32_t fa, fs;
            {
                const int nd = nb + (lane & 7);
                const int p0 = ms->off[nd], p1 = ms->off[nd + 1];
                const bool full = p0 >= s && p1 <= e && p1 > p0;
                const bool fst = p0 < s && p1 > s;
                const bool lst = p0 >= s && p0 < e && p1 > e;
                fa = full ? sb + SM_AGG + sw<80>(nd, lane >> 3)
                          : (fst ? ring + 4608 : lst ? ring + 4864 : sb + SM_TRASH) + (lane >> 3) * 16;
                fs = full ? 10240 : 128;
            }
            float acc[8][4];
#pragma unroll
            for (int m = 0; m < 8; m++)
#pragma unroll
                for (int k = 0; k < 4; k++) acc[m][k] = 0.f;
            uint32_t qf[4][4];
            const uint32_t qa = sb + SM_Q + sw<80>(min(nb + (int)(lane & 7), 79), lane >> 3);
#pragma unroll
            for (int j = 0; j < 4; j++) ldsm4t(qf[j], (qa ^ ((j & 1) << 6)) + (j >> 1) * 10240);
            uint32_t q0, q1, ss0, ss1;
            uint2 e0, e1;
            int last;
            float c[2][2][2][4];
            auto top = [&]() {
                const uint32_t u = tb + g - o0;
                q0 = (u < cn0 ? 0x3F00u : 0u) | (u - cn0 < cn1 ? 0x3F000000u : 0u);
                q1 = (u + 8 < cn0 ? 0x3F00u : 0u) | (u + 8 - cn0 < cn1 ? 0x3F000000u : 0u);
                tb += 16;
                fidx(tb);
                cp_wait<1>();
                __syncwarp();
                e0 = lds64(ring + 4096 + lane * 8);
                e1 = lds64(ring + 4096 + 256 + lane * 8);
            };
            auto stageA = [&](int j, float (&cc)[2][2][4]) {
                if (j == 2) { cp_wait<1>(); __syncwarp(); }
#pragma unroll
                for (int mm = 0; mm < 2; mm++) {
                    const int m = 2 * j + mm;
                    const uint4 wf = lds128(w3a + m * 512);
                    ldsm4tf(cc[mm][0], (lz ^ ((m & 3) << 5)) + (m >> 2) * 2048);
                    ldsm4tf(cc[mm][1], (lz ^ ((m & 3) << 5)) + (m >> 2) * 2048 + 1024);
                    mma8(cc[mm][0], qf[j][2 * mm], qf[j][2 * mm + 1], q0);
                    mma8(cc[mm][1], qf[j][2 * mm], qf[j][2 * mm + 1], q1);
                    mma16(cc[mm][0], wf.x, wf.y, wf.z, wf.w, e0.x, e0.y);
                    mma16(cc[mm][1], wf.x, wf.y, wf.z, wf.w, e1.x, e1.y);
                }
                if (j & 1) {
                    __syncwarp();
                    if (j == 1) fetchE(last);
                    fetchP(j >> 1, last);
                    cp_commit();
                }
            };
            auto stageB = [&](int j, float (&cc)[2][2][4]) {
#pragma unroll
                for (int mm = 0; mm < 2; mm++) {
                    const uint32_t a0 = pack2(silu_h(cc[mm][0][0]), silu_h(cc[mm][0][1]));
                    const uint32_t a1 = pack2(silu_h(cc[mm][0][2]), silu_h(cc[mm][0][3]));
                    const uint32_t a2 = pack2(silu_h(cc[mm][1][0]), silu_h(cc[mm][1][1]));
                    const uint32_t a3 = pack2(silu_h(cc[mm][1][2]), silu_h(cc[mm][1][3]));
                    mma16(acc[2 * j + mm], a0, a1, a2, a3, ss0, ss1);
                }
            };
            top();
            stageA(0, c[0]);
#pragma unroll 1
            for (;;) {
                ss0 = movm(q0);
                ss1 = movm(q1);
                last = tb >= hi;
                stageA(1, c[1]); stageB(0, c[0]);
                stageA(2, c[0]); stageB(1, c[1]);
                stageA(3, c[1]); stageB(2, c[0]);
                top();
                stageA(0, c[0]);
                stageB(3, c[1]);
                if (last) break;
            }
#pragma unroll
            for (int j = 0; j < 4; j++)
                stsm4t((fa ^ ((j & 1) << 6)) + (j >> 1) * fs, pack2(acc[2 * j][0], acc[2 * j][1]), pack2(acc[2 * j][2], acc[2 * j][3]),
                       pack2(acc[2 * j + 1][0], acc[2 * j + 1][1]), pack2(acc[2 * j + 1][2], acc[2 * j + 1][3]));
            lo = hi;
            if (lo < e) {
                cp_wait<0>();
                __syncwarp();
                fidx(lo & ~15);
                first_fetch();
            }
        }
    }
    if (warp >= 8) {
        const int tb = tid - 256;
        const int r1 = (warp - 8) * 2 + (lane >> 4);
        const unsigned hl = lane & 15;
        const bool slow = ms->anyovf;
        bar_sync<0, 512>();
        if (tb == 0) TSTAMP(21);
        const uint32_t desc = lds32(sb + SM_MISC + r1 * 4);
        uint4 u = lds128(sb + SM_RING + r1 * SLOT + 4864 + hl * 16);
        uint4 u2 = lds128(sb + SM_RING + min(r1 + 1, 15) * SLOT + 4608 + hl * 16);
        if (desc) {
            const int nl = desc & 255;
            float v[8];
            v[0] = __uint_as_float(u.x << 16); v[1] = __uint_as_float(u.x & 0xffff0000u);
            v[2] = __uint_as_float(u.y << 16); v[3] = __uint_as_float(u.y & 0xffff0000u);
            v[4] = __uint_as_float(u.z << 16); v[5] = __uint_as_float(u.z & 0xffff0000u);
            v[6] = __uint_as_float(u.w << 16); v[7] = __uint_as_float(u.w & 0xffff0000u);
            for (uint32_t mk = desc >> 8; mk; mk &= mk - 1) {
                const int r2 = __ffs(mk) - 1;
                if (r2 != r1 + 1) u2 = lds128(sb + SM_RING + r2 * SLOT + 4608 + hl * 16);
                v[0] += __uint_as_float(u2.x << 16); v[1] += __uint_as_float(u2.x & 0xffff0000u);
                v[2] += __uint_as_float(u2.y << 16); v[3] += __uint_as_float(u2.y & 0xffff0000u);
                v[4] += __uint_as_float(u2.z << 16); v[5] += __uint_as_float(u2.z & 0xffff0000u);
                v[6] += __uint_as_float(u2.w << 16); v[7] += __uint_as_float(u2.w & 0xffff0000u);
            }
            *reinterpret_cast<uint4*>(smem + SM_AGG + sw<80>(nl, hl)) =
                make_uint4(pack2(v[0], v[1]), pack2(v[2], v[3]), pack2(v[4], v[5]), pack2(v[6], v[7]));
        }
        if (slow) {
            __threadfence();
            bar_sync<2, 256>();
            float* ext = reinterpret_cast<float*>(smem + SM_EXT);
            for (int i = tb; i < 80 * 128; i += 256) ext[i] = 0.f;
            bar_sync<2, 256>();
            const char* Pb = reinterpret_cast<const char*>(sc->P);
            for (int w = -1; w < NWR; w++) {
                const int cnt = w < 0 ? ms->total - CAP : ms->wovf[w];
                for (int k = warp - 8; k < cnt; k += 8) {
                    uint2 en;
                    const uint2* ep = w < 0 ? sc->spill + cta * NSPILL + k : sc->ovf + w * EPC + k;
                    asm volatile("ld.relaxed.gpu.global.v2.u32 {%0,%1}, [%2];" : "=r"(en.x), "=r"(en.y) : "l"(ep) : "memory");
                    const int nl = (int)en.x - node0;
                    const uint32_t eid = en.y;
                    if (nl < 0 || nl >= NPC) continue;
                    const uint32_t sn = src[eid];
                    for (int u = 0; u < 4; u++) {
                        const int f = lane * 4 + u;
                        float h = 0.f;
                        for (int kk = 0; kk < 16; kk++)
                            h = fmaf(__bfloat162float(e_attr[(size_t)eid * 16 + kk]), __bfloat162float(w_msg[(256 + kk) * 128 + f]), h);
                        h += __bfloat162float(*reinterpret_cast<const __nv_bfloat16*>(smem + SM_Q + sw<80>(nl, f >> 3) + (f & 7) * 2));
                        h = 0.5f * h + __bfloat162float(*reinterpret_cast<const __nv_bfloat16*>(Pb + sn * 256 + f * 2));
                        atomicAdd(&ext[nl * 128 + f], __bfloat162float(__float2bfloat16_rn(silu_h(h))));
                    }
                }
            }
            bar_sync<2, 256>();
            for (int i = tb; i < 80 * 128; i += 256) {
                const int r = i >> 7, f = i & 127;
                __nv_bfloat16* pp = reinterpret_cast<__nv_bfloat16*>(smem + SM_AGG + sw<80>(r, f >> 3) + (f & 7) * 2);
                *pp = __float2bfloat16_rn(__bfloat162float(*pp) + 0.5f * ext[i]);
            }
        }
        fence_async();
        bar_arrive<4, 512>();
        return;
    }
    {
        const int wg = warp >> 2;
        float a0[40];
        bar_arrive<0, 512>();
        fence_async();
#pragma unroll
        for (int j = 0; j < 10; j++) {
            const float4 v = *reinterpret_cast<const float4*>(smem + r_off(j) + tid * 16);
            a0[4 * j] = v.x; a0[4 * j + 1] = v.y; a0[4 * j + 2] = v.z; a0[4 * j + 3] = v.w;
        }
        mbar_wait(smem_u32(ms->mbar) + 16);
        bar_sync<4, 512>();
        if (tid == 0) TSTAMP(14);
        asm volatile("" : ACC40(a0)::"memory");
        wgmma_issue_split(a0, sb + SM_WU + wg * 32768 + 16384, sb + SM_AGG);
        auto emit = [&](int j0, int j1, const CUtensorMap* tm) {
#pragma unroll
            for (int j = j0; j < j1; j += 2) {
                uint32_t r[4];
#pragma unroll
                for (int k = 0; k < 4; k++) r[k] = pack2(silu_h(a0[4 * j + 2 * k]), silu_h(a0[4 * j + 2 * k + 1]));
                stsm4t(sb + SM_OUT + tile_a + j * 1024, r[0], r[1], r[2], r[3]);
            }
            fence_async();
            if (wg == 0) bar_sync<1, 128>(); else bar_sync<3, 128>();
            if ((tid & 127) == 0) {
                tma_store(tm, sb + SM_OUT + wg * 10240 + j0 * 1024, wg * 64, node0 + j0 * 8);
                asm volatile("cp.async.bulk.commit_group;" ::: "memory");
            }
        };
        asm volatile("wgmma.wait_group.sync.aligned 1;" : ACC8(a0, 0), ACC8(a0, 8), ACC8(a0, 16)::"memory");
        if (tid == 0) TSTAMP(26);
        emit(0, 6, &tm_out);
        asm volatile("wgmma.wait_group.sync.aligned 0;" : ACC8(a0, 24), ACC8(a0, 32)::"memory");
        emit(6, 10, &tm_out2);
        if ((tid & 127) == 0) asm volatile("cp.async.bulk.wait_group.read 0;" ::: "memory");
    }
    if (tid == 0) TSTAMP(12);
}

}

typedef CUresult (*EncodeFn)(CUtensorMap*, CUtensorMapDataType, cuuint32_t, void*, const cuuint64_t*, const cuuint64_t*,
                             const cuuint32_t*, const cuuint32_t*, CUtensorMapInterleave, CUtensorMapSwizzle,
                             CUtensorMapL2promotion, CUtensorMapFloatOOBfill);

static void make_map(EncodeFn enc, CUtensorMap* tm, const void* base, int rows, int box_rows) {
    const cuuint64_t dims[2] = {128, (cuuint64_t)rows};
    const cuuint64_t strides[1] = {256};
    const cuuint32_t box[2] = {64, (cuuint32_t)box_rows};
    const cuuint32_t estr[2] = {1, 1};
    enc(tm, CU_TENSOR_MAP_DATA_TYPE_BFLOAT16, 2, const_cast<void*>(base), dims, strides, box, estr, CU_TENSOR_MAP_INTERLEAVE_NONE,
        CU_TENSOR_MAP_SWIZZLE_128B, CU_TENSOR_MAP_L2_PROMOTION_NONE, CU_TENSOR_MAP_FLOAT_OOB_FILL_NONE);
}

extern "C" void kernel_launch(void* const* d_in, const int* in_sizes, int n_in, void* d_out, int out_size) {
    const __nv_bfloat16* x = (const __nv_bfloat16*)d_in[0];
    const __nv_bfloat16* e_attr = (const __nv_bfloat16*)d_in[1];
    const int* src = (const int*)d_in[2];
    const int* dst = (const int*)d_in[3];
    const __nv_bfloat16* w_msg = (const __nv_bfloat16*)d_in[4];

    static int fused = -1;
    static Scratch* sc = nullptr;
    static EncodeFn enc = nullptr;
    if (fused < 0) {
        cudaFuncSetAttribute(mpnn_kernel<1>, cudaFuncAttributeMaxDynamicSharedMemorySize, SM_ALLOC);
        cudaFuncSetAttribute(mpnn_kernel<2>, cudaFuncAttributeMaxDynamicSharedMemorySize, SM_ALLOC);
        cudaFuncSetAttribute(mpnn_kernel<3>, cudaFuncAttributeMaxDynamicSharedMemorySize, SM_ALLOC);
        int dev = 0, sms = 0, occ = 0;
        cudaGetDevice(&dev);
        cudaDeviceGetAttribute(&sms, cudaDevAttrMultiProcessorCount, dev);
        cudaOccupancyMaxActiveBlocksPerMultiprocessor(&occ, mpnn_kernel<3>, THREADS, SM_ALLOC);
        cudaGetSymbolAddress((void**)&sc, g_sc);
        cudaDriverEntryPointQueryResult qr;
        cudaGetDriverEntryPoint("cuTensorMapEncodeTiled", (void**)&enc, cudaEnableDefault, &qr);
        fused = (sms * occ >= NCTA) ? 1 : 0;
    }
    CUtensorMap tm_wm, tm_wu, tm_mail, tm_p, tm_out, tm_out2;
    make_map(enc, &tm_out, d_out, NN, 48);
    make_map(enc, &tm_out2, d_out, NN, NPC - 48);
    make_map(enc, &tm_p, sc->P, NN, NPC);
    {
        const cuuint64_t dims[2] = {RCHUNK * 4, NCTA};
        const cuuint64_t strides[1] = {RCHUNK * 16};
        const cuuint32_t box[2] = {32, NCTA};
        const cuuint32_t estr[2] = {1, 1};
        enc(&tm_mail, CU_TENSOR_MAP_DATA_TYPE_UINT32, 2, sc->mail, dims, strides, box, estr, CU_TENSOR_MAP_INTERLEAVE_NONE,
            CU_TENSOR_MAP_SWIZZLE_NONE, CU_TENSOR_MAP_L2_PROMOTION_NONE, CU_TENSOR_MAP_FLOAT_OOB_FILL_NONE);
    }
    make_map(enc, &tm_wm, d_in[4], 272, 128);
    make_map(enc, &tm_wu, d_in[5], 256, 128);
    if (fused) {
        mpnn_kernel<3><<<NCTA, THREADS, SM_ALLOC, cudaStreamPerThread>>>(x, e_attr, src, dst, w_msg, sc, tm_wm, tm_wu, tm_mail, tm_p, tm_out, tm_out2);
    } else {
        mpnn_kernel<1><<<NCTA, THREADS, SM_ALLOC, cudaStreamPerThread>>>(x, e_attr, src, dst, w_msg, sc, tm_wm, tm_wu, tm_mail, tm_p, tm_out, tm_out2);
        mpnn_kernel<2><<<NCTA, THREADS, SM_ALLOC, cudaStreamPerThread>>>(x, e_attr, src, dst, w_msg, sc, tm_wm, tm_wu, tm_mail, tm_p, tm_out, tm_out2);
    }
}
```

```cpp
#include <cuda_runtime.h>
#include <cuda.h>
#include <cuda_bf16.h>
#include <stdint.h>
#include <stddef.h>

namespace {

constexpr int NN = 10000;
constexpr int EE = 160000;
constexpr int NCTA = 132;
constexpr int NPC = 76;
constexpr int NWR = 125;
constexpr int EPC = 1280;
constexpr int THREADS = 512;
constexpr int MCAP = 31;
constexpr int SCHUNK = NCTA * 8;
constexpr int RCHUNK = 128 * 8;
constexpr int CAP = 2048;
constexpr int NSPILL = NWR * MCAP - CAP;

static_assert(NCTA * NPC >= NN, "nodes");
static_assert(NWR * EPC == EE, "edges");
static_assert(NN <= 16384 && EPC < 2047 && NPC < 80, "entry packing");

constexpr int SLOT = 5120;
constexpr int SM_RING = 0;
constexpr int SM_W12 = 0;
constexpr int SM_WOFF = 65536;
constexpr int SM_W3S = SM_WOFF + 4096;
constexpr int SM_OUT = 0;
constexpr int SM_EXT = 0;
constexpr int SM_AGG = 16 * SLOT;
constexpr int SM_WU = SM_AGG + 20480;
constexpr int SM_X = SM_WU + 65536;
constexpr int SM_ZL = SM_X + 8192;
constexpr int SM_Q = SM_X + 20480;
constexpr int SM_LIST = SM_Q + 20480;
constexpr int LISTB = (CAP + 64) * 4;
constexpr int SM_EID = SM_LIST + LISTB;
constexpr int SM_W3F = SM_EID + LISTB;
constexpr int SM_MISC = SM_W3F + 4096;
constexpr int SM_TRASH = SM_MISC + 2048;
constexpr int SM_TOTAL = SM_TRASH + 256;
constexpr int SM_ALLOC = SM_TOTAL;
static_assert(2 * LISTB >= SCHUNK * 16, "staging");
static_assert(SM_ALLOC <= 232448, "smem");

struct Misc {
    int cnt[NCTA];
    int ncnt[128];
    int off[100];
    int ovf;
    int anyovf;
    int total;
    int pad;
    int wovf[128];
    uint4 pad2;
    unsigned long long mbar[4];
};
constexpr int MISC_ZERO16 = 124;
static_assert(offsetof(Misc, mbar) == MISC_ZERO16 * 16, "misc layout");
static_assert(sizeof(Misc) <= 2048, "misc");

struct Scratch {
    uint4 P[NN * 16];
    uint4 mail[NCTA * RCHUNK];
    uint2 ovf[NWR * EPC];
    uint2 spill[NCTA * NSPILL];
    unsigned sync[64];
};
__device__ Scratch g_sc;

#define TSTAMP(i) do {} while (0)

__device__ __forceinline__ uint32_t smem_u32(const void* p) { return (uint32_t)__cvta_generic_to_shared(p); }

template <int ROWS>
__device__ __forceinline__ uint32_t sw(int row, int chunk) {
    return (uint32_t)((chunk >> 3) * (ROWS * 128) + row * 128 + (((chunk & 7) ^ (row & 7)) << 4));
}

__device__ __forceinline__ uint32_t w3sw(unsigned row, unsigned chunk) {
    return (chunk >> 3) * 2048 + row * 128 + (((chunk & 7) ^ ((row & 1) | ((row >> 1) & 6))) << 4);
}
__device__ __forceinline__ constexpr int r_off(int j) {
    return j < 4 ? SM_WU + j * 4096 : j < 8 ? SM_WU + 32768 + (j - 4) * 4096 : SM_X + (j - 8) * 4096;
}
__device__ __forceinline__ void cp16(uint32_t dst, const void* src) {
    asm volatile("cp.async.cg.shared.global [%0], [%1], 16;" ::"r"(dst), "l"(src) : "memory");
}
template <int SCALE, int OFF>
__device__ __forceinline__ void cp16g(uint32_t dst, const void* base, uint32_t idx, int skip) {
    asm volatile("{.reg .pred p; .reg .b64 a; mad.wide.u32 a, %2, %4, %1; setp.eq.s32 p, %3, 0;\n"
                 "@p cp.async.cg.shared.global [%0], [a+%5], 16;}"
                 ::"r"(dst), "l"(base), "r"(idx), "r"(skip), "n"(SCALE), "n"(OFF) : "memory");
}
__device__ __forceinline__ void cp_commit() { asm volatile("cp.async.commit_group;" ::: "memory"); }
template <int N>
__device__ __forceinline__ void cp_wait() { asm volatile("cp.async.wait_group %0;" ::"n"(N) : "memory"); }
template <int ID, int N>
__device__ __forceinline__ void bar_sync() { asm volatile("bar.sync %0, %1;" ::"n"(ID), "n"(N) : "memory"); }
template <int ID, int N>
__device__ __forceinline__ void bar_arrive() { asm volatile("bar.arrive %0, %1;" ::"n"(ID), "n"(N) : "memory"); }
__device__ __forceinline__ void fence_async() { asm volatile("fence.proxy.async.shared::cta;" ::: "memory"); }

__device__ __forceinline__ void ldsm4t(uint32_t (&r)[4], uint32_t a) {
    asm volatile("ldmatrix.sync.aligned.m8n8.x4.trans.shared.b16 {%0,%1,%2,%3}, [%4];"
                 : "=r"(r[0]), "=r"(r[1]), "=r"(r[2]), "=r"(r[3]) : "r"(a));
}
__device__ __forceinline__ uint4 lds128(uint32_t a) {
    uint4 v;
    asm volatile("ld.shared.v4.u32 {%0,%1,%2,%3}, [%4];" : "=r"(v.x), "=r"(v.y), "=r"(v.z), "=r"(v.w) : "r"(a));
    return v;
}
__device__ __forceinline__ uint2 lds64(uint32_t a) {
    uint2 v;
    asm volatile("ld.shared.v2.u32 {%0,%1}, [%2];" : "=r"(v.x), "=r"(v.y) : "r"(a));
    return v;
}
__device__ __forceinline__ uint32_t lds32(uint32_t a) {
    uint32_t v;
    asm volatile("ld.shared.u32 %0, [%1];" : "=r"(v) : "r"(a));
    return v;
}
__device__ __forceinline__ uint32_t lds16(uint32_t a) {
    uint32_t v;
    asm volatile("ld.shared.u16 %0, [%1];" : "=r"(v) : "r"(a));
    return v;
}
__device__ __forceinline__ void sts32(uint32_t a, uint32_t v) {
    asm volatile("st.shared.u32 [%0], %1;" ::"r"(a), "r"(v) : "memory");
}
__device__ __forceinline__ void stsm4t(uint32_t a, uint32_t r0, uint32_t r1, uint32_t r2, uint32_t r3) {
    asm volatile("stmatrix.sync.aligned.m8n8.x4.trans.shared.b16 [%0], {%1,%2,%3,%4};"
                 ::"r"(a), "r"(r0), "r"(r1), "r"(r2), "r"(r3) : "memory");
}
__device__ __forceinline__ void mma16(float (&d)[4], const uint32_t a0, const uint32_t a1, const uint32_t a2,
                                      const uint32_t a3, const uint32_t b0, const uint32_t b1) {
    asm("mma.sync.aligned.m16n8k16.row.col.f32.bf16.bf16.f32 {%0,%1,%2,%3}, {%4,%5,%6,%7}, {%8,%9}, {%0,%1,%2,%3};"
        : "+f"(d[0]), "+f"(d[1]), "+f"(d[2]), "+f"(d[3])
        : "r"(a0), "r"(a1), "r"(a2), "r"(a3), "r"(b0), "r"(b1));
}
__device__ __forceinline__ void mma8(float (&d)[4], const uint32_t a0, const uint32_t a1, const uint32_t b0) {
    asm("mma.sync.aligned.m16n8k8.row.col.f32.bf16.bf16.f32 {%0,%1,%2,%3}, {%4,%5}, {%6}, {%0,%1,%2,%3};"
        : "+f"(d[0]), "+f"(d[1]), "+f"(d[2]), "+f"(d[3])
        : "r"(a0), "r"(a1), "r"(b0));
}
__device__ __forceinline__ uint32_t movm(uint32_t a) {
    uint32_t d;
    asm("movmatrix.sync.aligned.m8n8.trans.b16 %0, %1;" : "=r"(d) : "r"(a));
    return d;
}
__device__ __forceinline__ void ldsm4tf(float (&r)[4], uint32_t a) {
    asm volatile("ldmatrix.sync.aligned.m8n8.x4.trans.shared.b16 {%0,%1,%2,%3}, [%4];"
                 : "=f"(r[0]), "=f"(r[1]), "=f"(r[2]), "=f"(r[3]) : "r"(a));
}
__device__ __forceinline__ int range_start(int r, int T) {
    const int t0 = ((r >> 2) * T) >> 2, n = ((((r >> 2) + 1) * T) >> 2) - t0, b = r & 3;
    return t0 + b * (n >> 2) + min(b, n & 3);
}
__device__ __forceinline__ uint32_t pack2(float lo, float hi) {
    uint32_t r;
    asm("cvt.rn.bf16x2.f32 %0, %1, %2;" : "=r"(r) : "f"(hi), "f"(lo));
    return r;
}
__device__ __forceinline__ uint32_t half2x(uint32_t a) {
    uint32_t r;
    asm("mul.rn.bf16x2 %0, %1, %2;" : "=r"(r) : "r"(a), "r"(0x3F003F00u));
    return r;
}
__device__ __forceinline__ float tanh_fast(float x) {
    float t;
    asm("tanh.approx.f32 %0, %1;" : "=f"(t) : "f"(x));
    return t;
}
__device__ __forceinline__ float silu_h(float h) { return fmaf(h, tanh_fast(h), h); }

__device__ __forceinline__ unsigned ld_relaxed32(const void* p) {
    unsigned v;
    asm volatile("ld.relaxed.gpu.global.u32 %0, [%1];" : "=r"(v) : "l"(p) : "memory");
    return v;
}
__device__ __forceinline__ unsigned ld_poll32(const void* p) {
    unsigned v;
    asm volatile("ld.acquire.gpu.global.u32 %0, [%1];" : "=r"(v) : "l"(p) : "memory");
    return v;
}
__device__ __forceinline__ uint32_t atoms_inc(uint32_t addr) {
    uint32_t r;
    asm volatile("atom.shared.add.u32 %0, [%1], 1;" : "=r"(r) : "r"(addr) : "memory");
    return r;
}
__device__ __forceinline__ void tma2d(uint32_t dst, const CUtensorMap* tm, int c0, int c1, uint32_t bar) {
    asm volatile("cp.async.bulk.tensor.2d.shared::cluster.global.mbarrier::complete_tx::bytes [%0], [%1, {%3, %4}], [%2];"
                 ::"r"(dst), "l"(tm), "r"(bar), "r"(c0), "r"(c1) : "memory");
}
__device__ __forceinline__ void tma_w(uint32_t dst, const CUtensorMap* tm, int row, uint32_t bar) {
    asm volatile("mbarrier.arrive.expect_tx.shared.b64 _, [%0], %1;" ::"r"(bar), "n"(32768) : "memory");
    tma2d(dst, tm, 0, row, bar);
    tma2d(dst + 32768, tm, 64, row, bar);
}
__device__ __forceinline__ void tma_store(const CUtensorMap* tm, uint32_t src, int c0, int c1) {
    asm volatile("cp.async.bulk.tensor.2d.global.shared::cta.bulk_group [%0, {%2, %3}], [%1];"
                 ::"l"(tm), "r"(src), "r"(c0), "r"(c1) : "memory");
}
__device__ __forceinline__ void mbar_wait(uint32_t bar) {
    uint32_t ok;
    int sp = 0;
    do {
        asm volatile("{.reg .pred p; mbarrier.try_wait.parity.shared.b64 p, [%1], 0; selp.u32 %0, 1, 0, p;}" : "=r"(ok) : "r"(bar) : "memory");
    } while (!ok && ++sp < (1 << 22));
}
template <int N>
__device__ __forceinline__ void cp_rows(uint32_t dst, const void* src) {
#pragma unroll
    for (int i = 0; i < N; i++)
        asm volatile("cp.async.cg.shared.global [%0], [%1], 16;" ::"r"(dst + i * 2048), "l"((const char*)src + i * 4096) : "memory");
}

#define ACC40(d)                                                                                              \
    "+f"(d[0]), "+f"(d[1]), "+f"(d[2]), "+f"(d[3]), "+f"(d[4]), "+f"(d[5]), "+f"(d[6]), "+f"(d[7]),         \
    "+f"(d[8]), "+f"(d[9]), "+f"(d[10]), "+f"(d[11]), "+f"(d[12]), "+f"(d[13]), "+f"(d[14]), "+f"(d[15]),   \
    "+f"(d[16]), "+f"(d[17]), "+f"(d[18]), "+f"(d[19]), "+f"(d[20]), "+f"(d[21]), "+f"(d[22]), "+f"(d[23]), \
    "+f"(d[24]), "+f"(d[25]), "+f"(d[26]), "+f"(d[27]), "+f"(d[28]), "+f"(d[29]), "+f"(d[30]), "+f"(d[31]), \
    "+f"(d[32]), "+f"(d[33]), "+f"(d[34]), "+f"(d[35]), "+f"(d[36]), "+f"(d[37]), "+f"(d[38]), "+f"(d[39])

__device__ __forceinline__ void wgmma_issue(float (&d)[40], uint32_t w_addr, uint32_t t_addr) {
    const uint32_t la = (w_addr >> 4) | 0x10000u, lb = (t_addr >> 4) | 0x10000u;
    asm volatile("wgmma.fence.sync.aligned;" ::: "memory");
#pragma unroll
    for (int ks = 0; ks < 8; ks++) {
        asm volatile(
            "{.reg .b64 da, db; .reg .pred p;\n"
            "setp.ne.s32 p, %43, 0;\n"
            "mov.b64 da, {%40, %42};\n"
            "mov.b64 db, {%41, %42};\n"
            "wgmma.mma_async.sync.aligned.m64n80k16.f32.bf16.bf16 "
            "{%0,%1,%2,%3,%4,%5,%6,%7,%8,%9,%10,%11,%12,%13,%14,%15,%16,%17,%18,%19,"
            "%20,%21,%22,%23,%24,%25,%26,%27,%28,%29,%30,%31,%32,%33,%34,%35,%36,%37,%38,%39},"
            "da, db, p, 1, 1, 1, 0;}"
            : ACC40(d)
            : "r"(la + ks * 128), "r"(lb + (ks >> 2) * 640 + (ks & 3) * 2), "r"(0x40000040u), "r"(ks > 0 ? 1 : 0));
    }
    asm volatile("wgmma.commit_group.sync.aligned;" ::: "memory");
}
#define ACC8(d, b) "+f"(d[b]), "+f"(d[b + 1]), "+f"(d[b + 2]), "+f"(d[b + 3]), "+f"(d[b + 4]), "+f"(d[b + 5]), "+f"(d[b + 6]), "+f"(d[b + 7])
__device__ __forceinline__ void wgmma_issue_split(float (&d)[40], uint32_t w_addr, uint32_t t_addr) {
    const uint32_t la = (w_addr >> 4) | 0x10000u, lb = (t_addr >> 4) | 0x10000u;
    asm volatile("wgmma.fence.sync.aligned;" ::: "memory");
#pragma unroll
    for (int ks = 0; ks < 8; ks++)
        asm volatile(
            "{.reg .b64 da, db;\n"
            "mov.b64 da, {%24, %26};\n"
            "mov.b64 db, {%25, %26};\n"
            "wgmma.mma_async.sync.aligned.m64n48k16.f32.bf16.bf16 "
            "{%0,%1,%2,%3,%4,%5,%6,%7,%8,%9,%10,%11,%12,%13,%14,%15,%16,%17,%18,%19,%20,%21,%22,%23},"
            "da, db, 1, 1, 1, 1, 0;}"
            : ACC8(d, 0), ACC8(d, 8), ACC8(d, 16)
            : "r"(la + ks * 128), "r"(lb + (ks >> 2) * 640 + (ks & 3) * 2), "r"(0x40000040u));
    asm volatile("wgmma.commit_group.sync.aligned;" ::: "memory");
#pragma unroll
    for (int ks = 0; ks < 8; ks++)
        asm volatile(
            "{.reg .b64 da, db;\n"
            "mov.b64 da, {%16, %18};\n"
            "mov.b64 db, {%17, %18};\n"
            "wgmma.mma_async.sync.aligned.m64n32k16.f32.bf16.bf16 "
            "{%0,%1,%2,%3,%4,%5,%6,%7,%8,%9,%10,%11,%12,%13,%14,%15},"
            "da, db, 1, 1, 1, 1, 0;}"
            : ACC8(d, 24), ACC8(d, 32)
            : "r"(la + ks * 128), "r"(lb + 384 + (ks >> 2) * 640 + (ks & 3) * 2), "r"(0x40000040u));
    asm volatile("wgmma.commit_group.sync.aligned;" ::: "memory");
}
template <int N>
__device__ __forceinline__ void wgmma_wait(float (&d)[40]) {
    asm volatile("wgmma.wait_group.sync.aligned %40;" : ACC40(d) : "n"(N) : "memory");
}
template <bool HALF>
__device__ __forceinline__ void store_tile(uint32_t a, const float (&d)[40]) {
#pragma unroll
    for (int j = 0; j < 10; j += 2) {
        uint32_t r[4];
#pragma unroll
        for (int k = 0; k < 4; k++) {
            r[k] = pack2(d[4 * j + 2 * k], d[4 * j + 2 * k + 1]);
            if (HALF) r[k] = half2x(r[k]);
        }
        stsm4t(a + j * 1024, r[0], r[1], r[2], r[3]);
    }
}

template <int MODE>
__global__ void __launch_bounds__(THREADS, 1)
mpnn_kernel(const __nv_bfloat16* __restrict__ e_attr,
            const int* __restrict__ src, const int* __restrict__ dst,
            const __nv_bfloat16* __restrict__ w_msg,
            Scratch* __restrict__ sc,
            const __grid_constant__ CUtensorMap tm_wm, const __grid_constant__ CUtensorMap tm_wu,
            const __grid_constant__ CUtensorMap tm_x, const __grid_constant__ CUtensorMap tm_p,
            const __grid_constant__ CUtensorMap tm_out, const __grid_constant__ CUtensorMap tm_out2) {
    extern __shared__ __align__(1024) uint8_t smem[];
    const uint32_t sb = smem_u32(smem);
    Misc* ms = reinterpret_cast<Misc*>(smem + SM_MISC);
    const unsigned tid = threadIdx.x, lane = tid & 31;
    __builtin_assume(tid < THREADS);
    const unsigned cta = blockIdx.x;
    __builtin_assume(cta < NCTA);
    uint32_t dv[5], sv[5];
    if ((MODE & 1) && cta < NWR && tid >= 256) {
        const int* dp = dst + cta * EPC - 256;
        const int* sp = src + cta * EPC - 256;
        asm volatile("ld.global.nc.v4.u32 {%0,%1,%2,%3}, [%4];" : "=r"(dv[0]), "=r"(dv[1]), "=r"(dv[2]), "=r"(dv[3]) : "l"(dp - 768 + tid * 4));
        asm volatile("ld.global.nc.u32 %0, [%1];" : "=r"(dv[4]) : "l"(dp + 1024 + tid));
        asm volatile("ld.global.nc.v4.u32 {%0,%1,%2,%3}, [%4];" : "=r"(sv[0]), "=r"(sv[1]), "=r"(sv[2]), "=r"(sv[3]) : "l"(sp - 768 + tid * 4));
        asm volatile("ld.global.nc.u32 %0, [%1];" : "=r"(sv[4]) : "l"(sp + 1024 + tid));
    }
    const int warp = __shfl_sync(0xffffffffu, tid >> 5, 0);
    if (tid == 0) TSTAMP(0);

    const unsigned g = lane >> 2, q = lane & 3;
    const int node0 = cta * NPC;
    const uint32_t tile_a = sw<80>(((lane >> 4) & 1) * 8 + (lane & 7), (warp & 7) * 2 + ((lane >> 3) & 1));

    if (warp >= 8) {
        const unsigned tb = tid - 256;
        __builtin_assume(tb < 256);
        const bool writer = (MODE & 1) && cta < NWR;
        bar_arrive<3, 512>();
        unsigned htarget = 0;
        if (tb == 0 && MODE == 3) htarget = ld_relaxed32(&sc->sync[32]);
        if (tb < MISC_ZERO16) reinterpret_cast<uint4*>(ms)[tb] = make_uint4(0, 0, 0, 0);
        bar_sync<2, 256>();
        if (tb == 0) TSTAMP(17);
        if (writer) {
            uint32_t own[5], pos[5];
#pragma unroll
            for (int i = 0; i < 5; i++) {
                own[i] = (dv[i] * 55189u) >> 22;
                pos[i] = atoms_inc(sb + SM_MISC + own[i] * 4);
            }
            if (tb == 0) TSTAMP(18);
            uint32_t pmax = 0;
#pragma unroll
            for (int i = 0; i < 5; i++) {
                const uint32_t nl = dv[i] - own[i] * NPC;
                const uint32_t el1 = i < 4 ? tb * 4 + i + 1 : tb + 1025;
                sts32(sb + SM_LIST + own[i] * 128 + (pos[i] < MCAP ? pos[i] * 4 + 4 : 0), (sv[i] * 128u + nl) * 2048u + el1);
                pmax = max(pmax, pos[i]);
            }
            if (pmax >= MCAP) {
#pragma unroll
                for (int i = 0; i < 5; i++) {
                    if (pos[i] >= MCAP) {
                        const int k = atomicAdd(&ms->ovf, 1);
                        sc->ovf[cta * EPC + k] = make_uint2(dv[i], cta * EPC + (i < 4 ? tb * 4 + i : tb + 1024));
                    }
                }
                __threadfence();
            }
            if (tb == 0) TSTAMP(8);
            bar_sync<2, 256>();
            if (tb == 0) TSTAMP(19);
            {
                const uint32_t hdr = (uint32_t)ms->ovf << 11;
                uint4* gm = sc->mail + (tb >> 3) * RCHUNK + cta * 8 + (tb & 7);
                uint4 v[5];
                uint32_t c[5];
#pragma unroll
                for (int i = 0; i < 5; i++) {
                    v[i] = lds128(sb + SM_LIST + tb * 16 + i * 4096);
                    c[i] = lds32(sb + SM_MISC + (tb >> 3) * 4 + i * 128);
                }
#pragma unroll
                for (int i = 0; i < 5; i++) {
                    if ((tb & 7) == 0) v[i].x = hdr | c[i];
                    if (i < 4 || tb < SCHUNK - 1024) gm[i * 32 * RCHUNK] = v[i];
                }
            }
            if (tb == 0) TSTAMP(9);
            bar_sync<2, 256>();
            if (tb == 0) TSTAMP(23);
        }
        if (!(MODE & 2)) return;
        if (MODE == 3) {
            if (tb == 0) {
                asm volatile("red.release.gpu.global.add.u32 [%0], 1;" ::"l"(&sc->sync[32]) : "memory");
                htarget = htarget - htarget % NCTA + NCTA;
                int sp = 0;
                while ((int)(ld_poll32(&sc->sync[32]) - htarget) < 0 && ++sp < (1 << 22)) {}
                TSTAMP(24);
            }
            bar_sync<2, 256>();
        }
        uint32_t w[2][8];
        {
            const uint4* mine = sc->mail + cta * RCHUNK + (tb >> 2) * 8 + (tb & 3);
            const uint4* mine2 = tb + 256 < NWR * 4 ? mine + 512 : mine;
            asm volatile("ld.relaxed.gpu.global.v4.u32 {%0,%1,%2,%3}, [%16];\n"
                         "ld.relaxed.gpu.global.v4.u32 {%8,%9,%10,%11}, [%17];\n"
                         "ld.relaxed.gpu.global.v4.u32 {%4,%5,%6,%7}, [%16+64];\n"
                         "ld.relaxed.gpu.global.v4.u32 {%12,%13,%14,%15}, [%17+64];"
                         : "=r"(w[0][0]), "=r"(w[0][1]), "=r"(w[0][2]), "=r"(w[0][3]), "=r"(w[0][4]), "=r"(w[0][5]), "=r"(w[0][6]), "=r"(w[0][7]),
                           "=r"(w[1][0]), "=r"(w[1][1]), "=r"(w[1][2]), "=r"(w[1][3]), "=r"(w[1][4]), "=r"(w[1][5]), "=r"(w[1][6]), "=r"(w[1][7])
                         : "l"(mine), "l"(mine2) : "memory");
        }
        uint32_t hd[2];
        hd[0] = __shfl_sync(0xffffffffu, w[0][0], lane & ~3u);
        hd[1] = __shfl_sync(0xffffffffu, w[1][0], lane & ~3u);
        if (tb + 256 >= NWR * 4) hd[1] = 0;
        if (tb == 0) TSTAMP(10);
        int lim[2];
#pragma unroll
        for (int b = 0; b < 2; b++) {
            if ((hd[b] & 0x7ffu) > MCAP) { ms->wovf[(tb >> 2) + 64 * b] = hd[b] >> 11; ms->anyovf = 1; }
            lim[b] = (int)(hd[b] & 0x7ffu) - (int)(tb & 3) * 4;
        }
        const bool second = __any_sync(0xffffffffu, max(lim[0], lim[1]) >= 16);
        const uint32_t dummy = (96u + lane) << 11;
        if ((tb & 3) == 0) w[0][0] = w[1][0] = dummy;
        uint32_t rk[2][8];
        const uint32_t nc = smem_u32(ms->ncnt);
        auto hist = [&](int i0) {
#pragma unroll
            for (int b = 0; b < 2; b++)
#pragma unroll
                for (int i = i0; i < i0 + 4; i++) {
                    w[b][i] = lim[b] >= (i & 3) + (i >> 2) * 16 ? w[b][i] : dummy;
                    rk[b][i] = atoms_inc(nc + ((w[b][i] >> 9) & 0x1fc));
                }
        };
        hist(0);
        if (second) hist(4);
        const uint32_t wo = sb + SM_WOFF + (warp - 8) * 512;
        sts32(wo + 384 + lane * 4, 1u << 20);
        if (tb == 0) TSTAMP(20);
        bar_sync<2, 256>();
        int total;
        {
            const int c0 = lds32(nc + lane * 12), c1 = lds32(nc + lane * 12 + 4), c2 = lds32(nc + lane * 12 + 8);
            int s = c0 + c1 + c2;
#pragma unroll
            for (int d = 1; d < 32; d <<= 1) {
                const int t = __shfl_up_sync(0xffffffffu, s, d);
                if (lane >= d) s += t;
            }
            sts32(wo + lane * 12, s - c2 - c1 - c0);
            sts32(wo + lane * 12 + 4, s - c2 - c1);
            sts32(wo + lane * 12 + 8, s - c2);
            total = __shfl_sync(0xffffffffu, s, 31);
            if (warp == 15) {
                ms->off[lane * 3] = min(s - c2 - c1 - c0, CAP);
                ms->off[lane * 3 + 1] = min(s - c2 - c1, CAP);
                ms->off[lane * 3 + 2] = min(s - c2, CAP);
                if (lane == 31) { ms->off[96] = min(s, CAP); ms->total = s; if (s > CAP) ms->anyovf = 1; }
                if (total < CAP) {
                    const uint32_t pa = sb + SM_LIST + (total + lane) * 4;
                    sts32(pa, 79u << 23);
                    sts32(pa + LISTB, 0u);
                    if (lane < 16) sts32(pa + 128, 79u << 23);
                }
            }
            __syncwarp();
        }
        if (tb == 0) TSTAMP(22);
        const uint32_t eb = (tb >> 2) * EPC - 1;
        auto scatter = [&](int i0) {
#pragma unroll
            for (int b = 0; b < 2; b++)
#pragma unroll
                for (int i = i0; i < i0 + 4; i++) rk[b][i] += lds32(wo + ((w[b][i] >> 9) & 0x1fc));
#pragma unroll
            for (int b = 0; b < 2; b++)
#pragma unroll
                for (int i = i0; i < i0 + 4; i++) {
                    const uint32_t a = sb + SM_LIST + min(rk[b][i], (uint32_t)(CAP + 63)) * 4;
                    sts32(a, (w[b][i] >> 18) | ((w[b][i] << 12) & 0x3f800000u));
                    sts32(a + LISTB, eb + b * (64 * EPC) + (w[b][i] & 0x7ff));
                }
            if (total > CAP) {
#pragma unroll
                for (int b = 0; b < 2; b++)
#pragma unroll
                    for (int i = i0; i < i0 + 4; i++)
                        if (rk[b][i] >= CAP && rk[b][i] < (1u << 20))
                            sc->spill[cta * NSPILL + rk[b][i] - CAP] = make_uint2(node0 + ((w[b][i] >> 11) & 127), eb + b * (64 * EPC) + (w[b][i] & 0x7ff));
            }
        };
        scatter(0);
        if (second) scatter(4);
        if (tb == 0) TSTAMP(11);
    } else {
        unsigned target = 0;
        const uint32_t mb = smem_u32(ms->mbar);
        {
            const unsigned r0 = tid >> 4, c0 = tid & 15;
            bar_sync<3, 512>();
            cp_rows<8>(sb + SM_W12 + sw<256>(r0, c0), reinterpret_cast<const uint4*>(w_msg) + tid);
            cp16(sb + SM_W3S + w3sw(r0, c0), reinterpret_cast<const uint4*>(w_msg) + 4096 + tid);
            if (tid == 32 && MODE == 3) target = ld_relaxed32(&sc->sync[0]);
            if (tid == 160) asm volatile("prefetch.tensormap [%0];" ::"l"(&tm_p) : "memory");
            if (tid == 64) asm volatile("prefetch.tensormap [%0];" ::"l"(&tm_wu) : "memory");
            if (tid == 96) asm volatile("prefetch.tensormap [%0];" ::"l"(&tm_out) : "memory");
            if (tid == 128) asm volatile("prefetch.tensormap [%0];" ::"l"(&tm_out2) : "memory");
            if (tid == 0) {
                asm volatile("mbarrier.init.shared.b64 [%0], 1;" ::"r"(mb) : "memory");
                asm volatile("mbarrier.init.shared.b64 [%0], 1;" ::"r"(mb + 8) : "memory");
                asm volatile("mbarrier.init.shared.b64 [%0], 1;" ::"r"(mb + 16) : "memory");
                asm volatile("mbarrier.init.shared.b64 [%0], 1;" ::"r"(mb + 24) : "memory");
                asm volatile("fence.mbarrier_init.release.cluster;" ::: "memory");
                asm volatile("mbarrier.arrive.expect_tx.shared.b64 _, [%0], %1;" ::"r"(mb + 24), "n"(20480) : "memory");
                tma2d(sb + SM_X, &tm_x, 0, node0, mb + 24);
                tma2d(sb + SM_X + 10240, &tm_x, 64, node0, mb + 24);
                if (MODE & 2) {
                    tma_w(sb + SM_W12 + 16384, &tm_wm, 128, mb);
                    tma_w(sb + SM_WU, &tm_wu, 0, mb + 8);
                }
            }
            cp_commit();
        }
        const int wg = warp >> 2;
        float a0[40];
        cp_wait<0>();
        fence_async();
        target = target - target % NCTA + NCTA;
        if (tid == 32) sts32(sb + SM_TRASH, target);
        bar_sync<1, 256>();
        mbar_wait(mb + 24);
        if (tid == 0) TSTAMP(1);
        if (MODE & 1) {
            wgmma_issue(a0, sb + SM_W12 + wg * 32768, sb + SM_X);
            wgmma_wait<0>(a0);
            if (tid == 0) TSTAMP(15);
            store_tile<true>(sb + SM_AGG + tile_a, a0);
            fence_async();
            bar_sync<1, 256>();
            if (tid == 0) TSTAMP(16);
            if (tid == 0) {
                tma_store(&tm_p, sb + SM_AGG, 0, node0);
                tma_store(&tm_p, sb + SM_AGG + 10240, 64, node0);
                asm volatile("cp.async.bulk.commit_group;" ::: "memory");
            }
        }
        if (!(MODE & 2)) {
            asm volatile("cp.async.bulk.wait_group 0;" ::: "memory");
            return;
        }
        float a1[40];
        mbar_wait(mb);
        wgmma_issue(a0, sb + SM_W12 + wg * 32768 + 16384, sb + SM_X);
        mbar_wait(mb + 8);
        wgmma_issue(a1, sb + SM_WU + wg * 32768, sb + SM_X);
        wgmma_wait<0>(a0);
        asm volatile("" : ACC40(a1)::"memory");
        bar_sync<1, 256>();
        if (tid == 0) {
            if (MODE == 3) {
                TSTAMP(4);
                asm volatile("cp.async.bulk.wait_group 0;" ::: "memory");
                TSTAMP(2);
                asm volatile("red.release.gpu.global.add.u32 [%0], 1;" ::"l"(&sc->sync[0]) : "memory");
                TSTAMP(3);
            }
        }
        store_tile<false>(sb + SM_Q + tile_a, a0);
        {
            uint32_t f[4];
            const unsigned r = lane & 7, mat = lane >> 3;
            ldsm4t(f, sb + SM_W3S + w3sw(4 * (r >> 1) + (r & 1) + 2 * (mat >> 1), warp * 2 + (mat & 1)));
            reinterpret_cast<uint4*>(smem + SM_W3F)[tid] = make_uint4(half2x(f[0]), half2x(f[1]), half2x(f[2]), half2x(f[3]));
        }
#pragma unroll
        for (int j = 0; j < 10; j++)
            *reinterpret_cast<float4*>(smem + r_off(j) + tid * 16) =
                make_float4(0.5f * a1[4 * j], 0.5f * a1[4 * j + 1], 0.5f * a1[4 * j + 2], 0.5f * a1[4 * j + 3]);
        if (tid >= 224) *reinterpret_cast<uint4*>(smem + SM_ZL + (lane >> 3) * 1024 + (lane & 7) * 16) = make_uint4(0, 0, 0, 0);
        if (tid == 0) TSTAMP(25);
        if (tid == 32 && MODE == 3) {
            TSTAMP(7);
            int sp = 0;
            while ((int)(ld_poll32(&sc->sync[0]) - target) < 0 && ++sp < (1 << 22)) {}
            TSTAMP(5);
        }
    }
    bar_sync<0, 512>();
    if (tid == 0) TSTAMP(6);

    const int M = ms->off[96];
    const int T = (M + 15) >> 4;
    const int rg = (warp & 3) * 4 + (warp >> 2);
    const int s = range_start(rg, T) * 16;
    const int e = min(range_start(rg + 1, T) * 16, M);
    const uint32_t ring = sb + SM_RING + rg * SLOT;
    {
        const unsigned fr = lane >> 3, fc = lane & 7;
        const char* Pb0 = reinterpret_cast<const char*>(sc->P) + ((fc ^ fr) << 4);
        const char* Pb1 = reinterpret_cast<const char*>(sc->P) + ((fc ^ fr ^ 4) << 4);
        const char* Eb = reinterpret_cast<const char*>(e_attr) + (lane & 1) * 16;
        asm volatile("" : "+l"(Pb0), "+l"(Pb1), "+l"(Eb));
        const uint32_t fdst = ring + lane * 16;
        const unsigned ledge = (lane & 6) | ((lane ^ (lane >> 3) ^ 1) & 1);
        const uint32_t lz = ((lane & 1) ? ring + ledge * 128 : sb + SM_ZL) + (((lane >> 4) ^ ledge) << 4);
        const uint32_t w3a = sb + SM_W3F + lane * 16;
        uint32_t sn[4], ei;
        auto fidx = [&](int tb) {
#pragma unroll
            for (int i = 0; i < 4; i++) sn[i] = lds16(sb + SM_LIST + (tb + fr) * 4 + i * 16);
            ei = lds32(sb + SM_EID + (tb + (lane >> 1)) * 4);
        };
        auto fetchP = [&](int h, int skip) {
#pragma unroll
            for (int i = 0; i < 4; i++) {
                if (h == 0) cp16g<256, 0>(fdst + i * 512, (i & 1) ? Pb1 : Pb0, sn[i], skip);
                else cp16g<256, 128>(fdst + 2048 + i * 512, (i & 1) ? Pb1 : Pb0, sn[i], skip);
            }
        };
        auto fetchE = [&](int skip) { cp16g<32, 0>(fdst + 4096, Eb, ei, skip); };
        int lo = s;
        auto first_fetch = [&]() {
            const int skip = lo >= e;
            fetchE(skip);
            fetchP(0, skip);
            cp_commit();
            fetchP(1, skip);
            cp_commit();
        };
        fidx(lo);
        if (warp >= 4) asm volatile("bar.sync %0, 256;" ::"r"(4 + (warp >> 2)) : "memory");
        fetchE(lo >= e);
        fetchP(0, lo >= e);
        cp_commit();
        if (warp < 12) asm volatile("bar.arrive %0, 256;" ::"r"(5 + (warp >> 2)) : "memory");
        fetchP(1, lo >= e);
        cp_commit();
        if (tid == 480) tma_w(sb + SM_WU + 16384, &tm_wu, 128, smem_u32(ms->mbar) + 16);
        {
            const int nd = warp * 5 + min(lane, 4u);
            unsigned em = __ballot_sync(0xffffffffu, ms->off[nd] == ms->off[nd + 1]) & 31u;
            while (em) {
                const int k = __ffs(em) - 1;
                em &= em - 1;
                *reinterpret_cast<uint2*>(smem + SM_AGG + sw<80>(warp * 5 + k, lane >> 1) + (lane & 1) * 8) = make_uint2(0, 0);
            }
        }
        if (lane == 0) {
            uint32_t desc = 0;
            if (s < e) {
                const int nl = lds32(sb + SM_LIST + (e - 1) * 4) >> 23;
                const int o1 = ms->off[nl + 1];
                if (ms->off[nl] >= s && o1 > e) {
                    desc = nl;
                    int s2 = e;
                    for (int r2 = rg + 1; s2 < o1; r2++) {
                        const int e2 = range_start(r2 + 1, T) * 16;
                        if (s2 < e2) desc |= 256u << r2;
                        s2 = e2;
                    }
                }
            }
            ms->cnt[rg] = desc;
        }
        while (lo < e) {
            int tb = lo & ~15;
            const int nb = lds32(sb + SM_LIST + lo * 4) >> 23;
            const int hi = min(e, ms->off[min(nb + 8, 96)]);
            const int o0 = ms->off[nb + 2 * q];
            const uint32_t cn0 = ms->off[nb + 2 * q + 1] - o0;
            const uint32_t cn1 = ms->off[nb + 2 * q + 2] - o0 - cn0;
            uint32_t fa, fs;
            {
                const int nd = nb + (lane & 7);
                const int p0 = ms->off[nd], p1 = ms->off[nd + 1];
                const bool full = p0 >= s && p1 <= e && p1 > p0;
                const bool fst = p0 < s && p1 > s;
                const bool lst = p0 >= s && p0 < e && p1 > e;
                fa = full ? sb + SM_AGG + sw<80>(nd, lane >> 3)
                          : (fst ? ring + 4608 : lst ? ring + 4864 : sb + SM_TRASH) + (lane >> 3) * 16;
                fs = full ? 10240 : 128;
            }
            float acc[8][4];
#pragma unroll
            for (int m = 0; m < 8; m++)
#pragma unroll
                for (int k = 0; k < 4; k++) acc[m][k] = 0.f;
            uint32_t qf[4][4];
            const uint32_t qa = sb + SM_Q + sw<80>(min(nb + (int)(lane & 7), 79), lane >> 3);
#pragma unroll
            for (int j = 0; j < 4; j++) ldsm4t(qf[j], (qa ^ ((j & 1) << 6)) + (j >> 1) * 10240);
            uint32_t q0, q1, ss0, ss1;
            uint2 e0, e1;
            int last;
            float c[2][2][2][4];
            auto top = [&]() {
                const uint32_t u = tb + g - o0;
                q0 = (u < cn0 ? 0x3F00u : 0u) | (u - cn0 < cn1 ? 0x3F000000u : 0u);
                q1 = (u + 8 < cn0 ? 0x3F00u : 0u) | (u + 8 - cn0 < cn1 ? 0x3F000000u : 0u);
                tb += 16;
                fidx(tb);
                cp_wait<1>();
                __syncwarp();
                e0 = lds64(ring + 4096 + lane * 8);
                e1 = lds64(ring + 4096 + 256 + lane * 8);
            };
            auto stageA = [&](int j, float (&cc)[2][2][4]) {
                if (j == 2) { cp_wait<1>(); __syncwarp(); }
#pragma unroll
                for (int mm = 0; mm < 2; mm++) {
                    const int m = 2 * j + mm;
                    const uint4 wf = lds128(w3a + m * 512);
                    ldsm4tf(cc[mm][0], (lz ^ ((m & 3) << 5)) + (m >> 2) * 2048);
                    ldsm4tf(cc[mm][1], (lz ^ ((m & 3) << 5)) + (m >> 2) * 2048 + 1024);
                    mma8(cc[mm][0], qf[j][2 * mm], qf[j][2 * mm + 1], q0);
                    mma8(cc[mm][1], qf[j][2 * mm], qf[j][2 * mm + 1], q1);
                    mma16(cc[mm][0], wf.x, wf.y, wf.z, wf.w, e0.x, e0.y);
                    mma16(cc[mm][1], wf.x, wf.y, wf.z, wf.w, e1.x, e1.y);
                }
                if (j & 1) {
                    __syncwarp();
                    if (j == 1) fetchE(last);
                    fetchP(j >> 1, last);
                    cp_commit();
                }
            };
            auto stageB = [&](int j, float (&cc)[2][2][4]) {
#pragma unroll
                for (int mm = 0; mm < 2; mm++) {
                    const uint32_t a0 = pack2(silu_h(cc[mm][0][0]), silu_h(cc[mm][0][1]));
                    const uint32_t a1 = pack2(silu_h(cc[mm][0][2]), silu_h(cc[mm][0][3]));
                    const uint32_t a2 = pack2(silu_h(cc[mm][1][0]), silu_h(cc[mm][1][1]));
                    const uint32_t a3 = pack2(silu_h(cc[mm][1][2]), silu_h(cc[mm][1][3]));
                    mma16(acc[2 * j + mm], a0, a1, a2, a3, ss0, ss1);
                }
            };
            top();
            stageA(0, c[0]);
#pragma unroll 1
            for (;;) {
                ss0 = movm(q0);
                ss1 = movm(q1);
                last = tb >= hi;
                stageA(1, c[1]); stageB(0, c[0]);
                stageA(2, c[0]); stageB(1, c[1]);
                stageA(3, c[1]); stageB(2, c[0]);
                top();
                stageA(0, c[0]);
                stageB(3, c[1]);
                if (last) break;
            }
#pragma unroll
            for (int j = 0; j < 4; j++)
                stsm4t((fa ^ ((j & 1) << 6)) + (j >> 1) * fs, pack2(acc[2 * j][0], acc[2 * j][1]), pack2(acc[2 * j][2], acc[2 * j][3]),
                       pack2(acc[2 * j + 1][0], acc[2 * j + 1][1]), pack2(acc[2 * j + 1][2], acc[2 * j + 1][3]));
            lo = hi;
            if (lo < e) {
                cp_wait<0>();
                __syncwarp();
                fidx(lo & ~15);
                first_fetch();
            }
        }
    }
    if (warp >= 8) {
        const int tb = tid - 256;
        const int r1 = (warp - 8) * 2 + (lane >> 4);
        const unsigned hl = lane & 15;
        const bool slow = ms->anyovf;
        bar_sync<0, 512>();
        if (tb == 0) TSTAMP(21);
        const uint32_t desc = lds32(sb + SM_MISC + r1 * 4);
        uint4 u = lds128(sb + SM_RING + r1 * SLOT + 4864 + hl * 16);
        uint4 u2 = lds128(sb + SM_RING + min(r1 + 1, 15) * SLOT + 4608 + hl * 16);
        if (desc) {
            const int nl = desc & 255;
            float v[8];
            v[0] = __uint_as_float(u.x << 16); v[1] = __uint_as_float(u.x & 0xffff0000u);
            v[2] = __uint_as_float(u.y << 16); v[3] = __uint_as_float(u.y & 0xffff0000u);
            v[4] = __uint_as_float(u.z << 16); v[5] = __uint_as_float(u.z & 0xffff0000u);
            v[6] = __uint_as_float(u.w << 16); v[7] = __uint_as_float(u.w & 0xffff0000u);
            for (uint32_t mk = desc >> 8; mk; mk &= mk - 1) {
                const int r2 = __ffs(mk) - 1;
                if (r2 != r1 + 1) u2 = lds128(sb + SM_RING + r2 * SLOT + 4608 + hl * 16);
                v[0] += __uint_as_float(u2.x << 16); v[1] += __uint_as_float(u2.x & 0xffff0000u);
                v[2] += __uint_as_float(u2.y << 16); v[3] += __uint_as_float(u2.y & 0xffff0000u);
                v[4] += __uint_as_float(u2.z << 16); v[5] += __uint_as_float(u2.z & 0xffff0000u);
                v[6] += __uint_as_float(u2.w << 16); v[7] += __uint_as_float(u2.w & 0xffff0000u);
            }
            *reinterpret_cast<uint4*>(smem + SM_AGG + sw<80>(nl, hl)) =
                make_uint4(pack2(v[0], v[1]), pack2(v[2], v[3]), pack2(v[4], v[5]), pack2(v[6], v[7]));
        }
        if (slow) {
            __threadfence();
            bar_sync<2, 256>();
            float* ext = reinterpret_cast<float*>(smem + SM_EXT);
            for (int i = tb; i < 80 * 128; i += 256) ext[i] = 0.f;
            bar_sync<2, 256>();
            const char* Pb = reinterpret_cast<const char*>(sc->P);
            for (int w = -1; w < NWR; w++) {
                const int cnt = w < 0 ? ms->total - CAP : ms->wovf[w];
                for (int k = warp - 8; k < cnt; k += 8) {
                    uint2 en;
                    const uint2* ep = w < 0 ? sc->spill + cta * NSPILL + k : sc->ovf + w * EPC + k;
                    asm volatile("ld.relaxed.gpu.global.v2.u32 {%0,%1}, [%2];" : "=r"(en.x), "=r"(en.y) : "l"(ep) : "memory");
                    const int nl = (int)en.x - node0;
                    const uint32_t eid = en.y;
                    if (nl < 0 || nl >= NPC) continue;
                    const uint32_t sn = src[eid];
                    for (int u = 0; u < 4; u++) {
                        const int f = lane * 4 + u;
                        float h = 0.f;
                        for (int kk = 0; kk < 16; kk++)
                            h = fmaf(__bfloat162float(e_attr[(size_t)eid * 16 + kk]), __bfloat162float(w_msg[(256 + kk) * 128 + f]), h);
                        h += __bfloat162float(*reinterpret_cast<const __nv_bfloat16*>(smem + SM_Q + sw<80>(nl, f >> 3) + (f & 7) * 2));
                        h = 0.5f * h + __bfloat162float(*reinterpret_cast<const __nv_bfloat16*>(Pb + sn * 256 + f * 2));
                        atomicAdd(&ext[nl * 128 + f], __bfloat162float(__float2bfloat16_rn(silu_h(h))));
                    }
                }
            }
            bar_sync<2, 256>();
            for (int i = tb; i < 80 * 128; i += 256) {
                const int r = i >> 7, f = i & 127;
                __nv_bfloat16* pp = reinterpret_cast<__nv_bfloat16*>(smem + SM_AGG + sw<80>(r, f >> 3) + (f & 7) * 2);
                *pp = __float2bfloat16_rn(__bfloat162float(*pp) + 0.5f * ext[i]);
            }
        }
        fence_async();
        bar_arrive<4, 512>();
        return;
    }
    {
        const int wg = warp >> 2;
        float a0[40];
        bar_arrive<0, 512>();
        fence_async();
#pragma unroll
        for (int j = 0; j < 10; j++) {
            const float4 v = *reinterpret_cast<const float4*>(smem + r_off(j) + tid * 16);
            a0[4 * j] = v.x; a0[4 * j + 1] = v.y; a0[4 * j + 2] = v.z; a0[4 * j + 3] = v.w;
        }
        mbar_wait(smem_u32(ms->mbar) + 16);
        bar_sync<4, 512>();
        if (tid == 0) TSTAMP(14);
        asm volatile("" : ACC40(a0)::"memory");
        wgmma_issue_split(a0, sb + SM_WU + wg * 32768 + 16384, sb + SM_AGG);
        auto emit = [&](int j0, int j1, const CUtensorMap* tm) {
#pragma unroll
            for (int j = j0; j < j1; j += 2) {
                uint32_t r[4];
#pragma unroll
                for (int k = 0; k < 4; k++) r[k] = pack2(silu_h(a0[4 * j + 2 * k]), silu_h(a0[4 * j + 2 * k + 1]));
                stsm4t(sb + SM_OUT + tile_a + j * 1024, r[0], r[1], r[2], r[3]);
            }
            fence_async();
            if (wg == 0) bar_sync<1, 128>(); else bar_sync<3, 128>();
            if ((tid & 127) == 0) {
                tma_store(tm, sb + SM_OUT + wg * 10240 + j0 * 1024, wg * 64, node0 + j0 * 8);
                asm volatile("cp.async.bulk.commit_group;" ::: "memory");
            }
        };
        asm volatile("wgmma.wait_group.sync.aligned 1;" : ACC8(a0, 0), ACC8(a0, 8), ACC8(a0, 16)::"memory");
        if (tid == 0) TSTAMP(26);
        emit(0, 6, &tm_out);
        asm volatile("wgmma.wait_group.sync.aligned 0;" : ACC8(a0, 24), ACC8(a0, 32)::"memory");
        emit(6, 10, &tm_out2);
        if ((tid & 127) == 0) asm volatile("cp.async.bulk.wait_group.read 0;" ::: "memory");
    }
    if (tid == 0) TSTAMP(12);
}

}

typedef CUresult (*EncodeFn)(CUtensorMap*, CUtensorMapDataType, cuuint32_t, void*, const cuuint64_t*, const cuuint64_t*,
                             const cuuint32_t*, const cuuint32_t*, CUtensorMapInterleave, CUtensorMapSwizzle,
                             CUtensorMapL2promotion, CUtensorMapFloatOOBfill);

static void make_map(EncodeFn enc, CUtensorMap* tm, const void* base, int rows, int box_rows) {
    const cuuint64_t dims[2] = {128, (cuuint64_t)rows};
    const cuuint64_t strides[1] = {256};
    const cuuint32_t box[2] = {64, (cuuint32_t)box_rows};
    const cuuint32_t estr[2] = {1, 1};
    enc(tm, CU_TENSOR_MAP_DATA_TYPE_BFLOAT16, 2, const_cast<void*>(base), dims, strides, box, estr, CU_TENSOR_MAP_INTERLEAVE_NONE,
        CU_TENSOR_MAP_SWIZZLE_128B, CU_TENSOR_MAP_L2_PROMOTION_NONE, CU_TENSOR_MAP_FLOAT_OOB_FILL_NONE);
}

extern "C" void kernel_launch(void* const* d_in, const int* in_sizes, int n_in, void* d_out, int out_size) {
    const __nv_bfloat16* e_attr = (const __nv_bfloat16*)d_in[1];
    const int* src = (const int*)d_in[2];
    const int* dst = (const int*)d_in[3];
    const __nv_bfloat16* w_msg = (const __nv_bfloat16*)d_in[4];

    static int fused = -1;
    static Scratch* sc = nullptr;
    static EncodeFn enc = nullptr;
    if (fused < 0) {
        cudaFuncSetAttribute(mpnn_kernel<1>, cudaFuncAttributeMaxDynamicSharedMemorySize, SM_ALLOC);
        cudaFuncSetAttribute(mpnn_kernel<2>, cudaFuncAttributeMaxDynamicSharedMemorySize, SM_ALLOC);
        cudaFuncSetAttribute(mpnn_kernel<3>, cudaFuncAttributeMaxDynamicSharedMemorySize, SM_ALLOC);
        int dev = 0, sms = 0, occ = 0;
        cudaGetDevice(&dev);
        cudaDeviceGetAttribute(&sms, cudaDevAttrMultiProcessorCount, dev);
        cudaOccupancyMaxActiveBlocksPerMultiprocessor(&occ, mpnn_kernel<3>, THREADS, SM_ALLOC);
        cudaGetSymbolAddress((void**)&sc, g_sc);
        cudaDriverEntryPointQueryResult qr;
        cudaGetDriverEntryPoint("cuTensorMapEncodeTiled", (void**)&enc, cudaEnableDefault, &qr);
        fused = (sms * occ >= NCTA) ? 1 : 0;
    }
    CUtensorMap tm_wm, tm_wu, tm_x, tm_p, tm_out, tm_out2;
    make_map(enc, &tm_out, d_out, NN, 48);
    make_map(enc, &tm_out2, d_out, NN, NPC - 48);
    make_map(enc, &tm_p, sc->P, NN, NPC);
    make_map(enc, &tm_x, d_in[0], NN, 80);
    make_map(enc, &tm_wm, d_in[4], 272, 128);
    make_map(enc, &tm_wu, d_in[5], 256, 128);
    if (fused) {
        mpnn_kernel<3><<<NCTA, THREADS, SM_ALLOC, cudaStreamPerThread>>>(e_attr, src, dst, w_msg, sc, tm_wm, tm_wu, tm_x, tm_p, tm_out, tm_out2);
    } else {
        mpnn_kernel<1><<<NCTA, THREADS, SM_ALLOC, cudaStreamPerThread>>>(e_attr, src, dst, w_msg, sc, tm_wm, tm_wu, tm_x, tm_p, tm_out, tm_out2);
        mpnn_kernel<2><<<NCTA, THREADS, SM_ALLOC, cudaStreamPerThread>>>(e_attr, src, dst, w_msg, sc, tm_wm, tm_wu, tm_x, tm_p, tm_out, tm_out2);
    }
}
```

```cpp
#include <cuda_runtime.h>
#include <cuda.h>
#include <cuda_bf16.h>
#include <stdint.h>
#include <stddef.h>

namespace {

constexpr int NN = 10000;
constexpr int EE = 160000;
constexpr int NCTA = 132;
constexpr int NPC = 76;
constexpr int NWR = 125;
constexpr int EPC = 1280;
constexpr int THREADS = 512;
constexpr int MCAP = 31;
constexpr int SCHUNK = NCTA * 8;
constexpr int RCHUNK = 128 * 8;
constexpr int CAP = 2048;
constexpr int NSPILL = NWR * MCAP - CAP;

static_assert(NCTA * NPC >= NN, "nodes");
static_assert(NWR * EPC == EE, "edges");
static_assert(NN <= 16384 && EPC < 2047 && NPC < 80, "entry packing");

constexpr int SLOT = 5120;
constexpr int SM_RING = 0;
constexpr int SM_W12 = 0;
constexpr int SM_WOFF = 65536;
constexpr int SM_W3S = SM_WOFF + 4096;
constexpr int SM_OUT = 0;
constexpr int SM_EXT = 0;
constexpr int SM_AGG = 16 * SLOT;
constexpr int SM_WU = SM_AGG + 20480;
constexpr int SM_X = SM_WU + 65536;
constexpr int SM_ZL = SM_X + 8192;
constexpr int SM_Q = SM_X + 20480;
constexpr int SM_LIST = SM_Q + 20480;
constexpr int LISTB = (CAP + 64) * 4;
constexpr int SM_EID = SM_LIST + LISTB;
constexpr int SM_W3F = SM_EID + LISTB;
constexpr int SM_MISC = SM_W3F + 4096;
constexpr int SM_TRASH = SM_MISC + 2048;
constexpr int SM_TOTAL = SM_TRASH + 256;
constexpr int SM_ALLOC = SM_TOTAL;
static_assert(2 * LISTB >= SCHUNK * 16, "staging");
static_assert(SM_ALLOC <= 232448, "smem");

struct Misc {
    int cnt[NCTA];
    int ncnt[128];
    int off[100];
    int ovf;
    int anyovf;
    int total;
    int pad;
    int wovf[128];
    uint4 pad2;
    unsigned long long mbar[4];
};
constexpr int MISC_ZERO16 = 124;
static_assert(offsetof(Misc, mbar) == MISC_ZERO16 * 16, "misc layout");
static_assert(sizeof(Misc) <= 2048, "misc");

struct Scratch {
    uint4 P[NN * 16];
    uint4 mail[NCTA * RCHUNK];
    uint2 ovf[NWR * EPC];
    uint2 spill[NCTA * NSPILL];
    unsigned sync[64];
};
__device__ Scratch g_sc;

#define TSTAMP(i) do {} while (0)

__device__ __forceinline__ uint32_t smem_u32(const void* p) { return (uint32_t)__cvta_generic_to_shared(p); }

template <int ROWS>
__device__ __forceinline__ uint32_t sw(int row, int chunk) {
    return (uint32_t)((chunk >> 3) * (ROWS * 128) + row * 128 + (((chunk & 7) ^ (row & 7)) << 4));
}

__device__ __forceinline__ uint32_t w3sw(unsigned row, unsigned chunk) {
    return (chunk >> 3) * 2048 + row * 128 + (((chunk & 7) ^ ((row & 1) | ((row >> 1) & 6))) << 4);
}
__device__ __forceinline__ constexpr int r_off(int j) {
    return j < 4 ? SM_WU + j * 4096 : j < 8 ? SM_WU + 32768 + (j - 4) * 4096 : SM_X + (j - 8) * 4096;
}
__device__ __forceinline__ void cp16(uint32_t dst, const void* src) {
    asm volatile("cp.async.cg.shared.global [%0], [%1], 16;" ::"r"(dst), "l"(src) : "memory");
}
template <int SCALE, int OFF>
__device__ __forceinline__ void cp16g(uint32_t dst, const void* base, uint32_t idx, int skip) {
    asm volatile("{.reg .pred p; .reg .b64 a; mad.wide.u32 a, %2, %4, %1; setp.eq.s32 p, %3, 0;\n"
                 "@p cp.async.cg.shared.global [%0], [a+%5], 16;}"
                 ::"r"(dst), "l"(base), "r"(idx), "r"(skip), "n"(SCALE), "n"(OFF) : "memory");
}
__device__ __forceinline__ void cp_commit() { asm volatile("cp.async.commit_group;" ::: "memory"); }
template <int N>
__device__ __forceinline__ void cp_wait() { asm volatile("cp.async.wait_group %0;" ::"n"(N) : "memory"); }
template <int ID, int N>
__device__ __forceinline__ void bar_sync() { asm volatile("bar.sync %0, %1;" ::"n"(ID), "n"(N) : "memory"); }
template <int ID, int N>
__device__ __forceinline__ void bar_arrive() { asm volatile("bar.arrive %0, %1;" ::"n"(ID), "n"(N) : "memory"); }
__device__ __forceinline__ void fence_async() { asm volatile("fence.proxy.async.shared::cta;" ::: "memory"); }

__device__ __forceinline__ void ldsm4t(uint32_t (&r)[4], uint32_t a) {
    asm volatile("ldmatrix.sync.aligned.m8n8.x4.trans.shared.b16 {%0,%1,%2,%3}, [%4];"
                 : "=r"(r[0]), "=r"(r[1]), "=r"(r[2]), "=r"(r[3]) : "r"(a));
}
__device__ __forceinline__ uint4 lds128(uint32_t a) {
    uint4 v;
    asm volatile("ld.shared.v4.u32 {%0,%1,%2,%3}, [%4];" : "=r"(v.x), "=r"(v.y), "=r"(v.z), "=r"(v.w) : "r"(a));
    return v;
}
__device__ __forceinline__ uint2 lds64(uint32_t a) {
    uint2 v;
    asm volatile("ld.shared.v2.u32 {%0,%1}, [%2];" : "=r"(v.x), "=r"(v.y) : "r"(a));
    return v;
}
__device__ __forceinline__ uint32_t lds32(uint32_t a) {
    uint32_t v;
    asm volatile("ld.shared.u32 %0, [%1];" : "=r"(v) : "r"(a));
    return v;
}
__device__ __forceinline__ uint32_t lds16(uint32_t a) {
    uint32_t v;
    asm volatile("ld.shared.u16 %0, [%1];" : "=r"(v) : "r"(a));
    return v;
}
__device__ __forceinline__ void sts32(uint32_t a, uint32_t v) {
    asm volatile("st.shared.u32 [%0], %1;" ::"r"(a), "r"(v) : "memory");
}
__device__ __forceinline__ void stsm4t(uint32_t a, uint32_t r0, uint32_t r1, uint32_t r2, uint32_t r3) {
    asm volatile("stmatrix.sync.aligned.m8n8.x4.trans.shared.b16 [%0], {%1,%2,%3,%4};"
                 ::"r"(a), "r"(r0), "r"(r1), "r"(r2), "r"(r3) : "memory");
}
__device__ __forceinline__ void mma16(float (&d)[4], const uint32_t a0, const uint32_t a1, const uint32_t a2,
                                      const uint32_t a3, const uint32_t b0, const uint32_t b1) {
    asm("mma.sync.aligned.m16n8k16.row.col.f32.bf16.bf16.f32 {%0,%1,%2,%3}, {%4,%5,%6,%7}, {%8,%9}, {%0,%1,%2,%3};"
        : "+f"(d[0]), "+f"(d[1]), "+f"(d[2]), "+f"(d[3])
        : "r"(a0), "r"(a1), "r"(a2), "r"(a3), "r"(b0), "r"(b1));
}
__device__ __forceinline__ void mma8(float (&d)[4], const uint32_t a0, const uint32_t a1, const uint32_t b0) {
    asm("mma.sync.aligned.m16n8k8.row.col.f32.bf16.bf16.f32 {%0,%1,%2,%3}, {%4,%5}, {%6}, {%0,%1,%2,%3};"
        : "+f"(d[0]), "+f"(d[1]), "+f"(d[2]), "+f"(d[3])
        : "r"(a0), "r"(a1), "r"(b0));
}
__device__ __forceinline__ uint32_t movm(uint32_t a) {
    uint32_t d;
    asm("movmatrix.sync.aligned.m8n8.trans.b16 %0, %1;" : "=r"(d) : "r"(a));
    return d;
}
__device__ __forceinline__ void ldsm4tf(float (&r)[4], uint32_t a) {
    asm volatile("ldmatrix.sync.aligned.m8n8.x4.trans.shared.b16 {%0,%1,%2,%3}, [%4];"
                 : "=f"(r[0]), "=f"(r[1]), "=f"(r[2]), "=f"(r[3]) : "r"(a));
}
__device__ __forceinline__ int range_start(int r, int T) {
    const int t0 = ((r >> 2) * T) >> 2, n = ((((r >> 2) + 1) * T) >> 2) - t0, b = r & 3;
    return t0 + b * (n >> 2) + min(b, n & 3);
}
__device__ __forceinline__ uint32_t pack2(float lo, float hi) {
    uint32_t r;
    asm("cvt.rn.bf16x2.f32 %0, %1, %2;" : "=r"(r) : "f"(hi), "f"(lo));
    return r;
}
__device__ __forceinline__ uint32_t half2x(uint32_t a) {
    uint32_t r;
    asm("mul.rn.bf16x2 %0, %1, %2;" : "=r"(r) : "r"(a), "r"(0x3F003F00u));
    return r;
}
__device__ __forceinline__ float tanh_fast(float x) {
    float t;
    asm("tanh.approx.f32 %0, %1;" : "=f"(t) : "f"(x));
    return t;
}
__device__ __forceinline__ float silu_h(float h) { return fmaf(h, tanh_fast(h), h); }

__device__ __forceinline__ unsigned ld_relaxed32(const void* p) {
    unsigned v;
    asm volatile("ld.relaxed.gpu.global.u32 %0, [%1];" : "=r"(v) : "l"(p) : "memory");
    return v;
}
__device__ __forceinline__ unsigned ld_poll32(const void* p) {
    unsigned v;
    asm volatile("ld.acquire.gpu.global.u32 %0, [%1];" : "=r"(v) : "l"(p) : "memory");
    return v;
}
__device__ __forceinline__ uint32_t atoms_inc(uint32_t addr) {
    uint32_t r;
    asm volatile("atom.shared.add.u32 %0, [%1], 1;" : "=r"(r) : "r"(addr) : "memory");
    return r;
}
__device__ __forceinline__ void tma2d(uint32_t dst, const CUtensorMap* tm, int c0, int c1, uint32_t bar) {
    asm volatile("cp.async.bulk.tensor.2d.shared::cluster.global.mbarrier::complete_tx::bytes [%0], [%1, {%3, %4}], [%2];"
                 ::"r"(dst), "l"(tm), "r"(bar), "r"(c0), "r"(c1) : "memory");
}
__device__ __forceinline__ void tma_w(uint32_t dst, const CUtensorMap* tm, int row, uint32_t bar) {
    asm volatile("mbarrier.arrive.expect_tx.shared.b64 _, [%0], %1;" ::"r"(bar), "n"(32768) : "memory");
    tma2d(dst, tm, 0, row, bar);
    tma2d(dst + 32768, tm, 64, row, bar);
}
__device__ __forceinline__ void tma_store(const CUtensorMap* tm, uint32_t src, int c0, int c1) {
    asm volatile("cp.async.bulk.tensor.2d.global.shared::cta.bulk_group [%0, {%2, %3}], [%1];"
                 ::"l"(tm), "r"(src), "r"(c0), "r"(c1) : "memory");
}
template <int OFF, int KB>
__device__ __forceinline__ void e_prefetch(const __nv_bfloat16* e_attr, unsigned cta) {
    static_assert((OFF + KB) * 1024 <= EPC * 32, "range");
    if (cta < NWR)
        asm volatile("cp.async.bulk.prefetch.L2.global [%0], %1;"
                     ::"l"(reinterpret_cast<const char*>(e_attr) + (size_t)cta * (EPC * 32) + OFF * 1024), "n"(KB * 1024) : "memory");
}
__device__ __forceinline__ void mbar_wait(uint32_t bar) {
    uint32_t ok;
    int sp = 0;
    do {
        asm volatile("{.reg .pred p; mbarrier.try_wait.parity.shared.b64 p, [%1], 0; selp.u32 %0, 1, 0, p;}" : "=r"(ok) : "r"(bar) : "memory");
    } while (!ok && ++sp < (1 << 22));
}
template <int N>
__device__ __forceinline__ void cp_rows(uint32_t dst, const void* src) {
#pragma unroll
    for (int i = 0; i < N; i++)
        asm volatile("cp.async.cg.shared.global [%0], [%1], 16;" ::"r"(dst + i * 2048), "l"((const char*)src + i * 4096) : "memory");
}

#define ACC40(d)                                                                                              \
    "+f"(d[0]), "+f"(d[1]), "+f"(d[2]), "+f"(d[3]), "+f"(d[4]), "+f"(d[5]), "+f"(d[6]), "+f"(d[7]),         \
    "+f"(d[8]), "+f"(d[9]), "+f"(d[10]), "+f"(d[11]), "+f"(d[12]), "+f"(d[13]), "+f"(d[14]), "+f"(d[15]),   \
    "+f"(d[16]), "+f"(d[17]), "+f"(d[18]), "+f"(d[19]), "+f"(d[20]), "+f"(d[21]), "+f"(d[22]), "+f"(d[23]), \
    "+f"(d[24]), "+f"(d[25]), "+f"(d[26]), "+f"(d[27]), "+f"(d[28]), "+f"(d[29]), "+f"(d[30]), "+f"(d[31]), \
    "+f"(d[32]), "+f"(d[33]), "+f"(d[34]), "+f"(d[35]), "+f"(d[36]), "+f"(d[37]), "+f"(d[38]), "+f"(d[39])

__device__ __forceinline__ void wgmma_issue(float (&d)[40], uint32_t w_addr, uint32_t t_addr) {
    const uint32_t la = (w_addr >> 4) | 0x10000u, lb = (t_addr >> 4) | 0x10000u;
    asm volatile("wgmma.fence.sync.aligned;" ::: "memory");
#pragma unroll
    for (int ks = 0; ks < 8; ks++) {
        asm volatile(
            "{.reg .b64 da, db; .reg .pred p;\n"
            "setp.ne.s32 p, %43, 0;\n"
            "mov.b64 da, {%40, %42};\n"
            "mov.b64 db, {%41, %42};\n"
            "wgmma.mma_async.sync.aligned.m64n80k16.f32.bf16.bf16 "
            "{%0,%1,%2,%3,%4,%5,%6,%7,%8,%9,%10,%11,%12,%13,%14,%15,%16,%17,%18,%19,"
            "%20,%21,%22,%23,%24,%25,%26,%27,%28,%29,%30,%31,%32,%33,%34,%35,%36,%37,%38,%39},"
            "da, db, p, 1, 1, 1, 0;}"
            : ACC40(d)
            : "r"(la + ks * 128), "r"(lb + (ks >> 2) * 640 + (ks & 3) * 2), "r"(0x40000040u), "r"(ks > 0 ? 1 : 0));
    }
    asm volatile("wgmma.commit_group.sync.aligned;" ::: "memory");
}
#define ACC8(d, b) "+f"(d[b]), "+f"(d[b + 1]), "+f"(d[b + 2]), "+f"(d[b + 3]), "+f"(d[b + 4]), "+f"(d[b + 5]), "+f"(d[b + 6]), "+f"(d[b + 7])
__device__ __forceinline__ void wgmma_issue_split(float (&d)[40], uint32_t w_addr, uint32_t t_addr) {
    const uint32_t la = (w_addr >> 4) | 0x10000u, lb = (t_addr >> 4) | 0x10000u;
    asm volatile("wgmma.fence.sync.aligned;" ::: "memory");
#pragma unroll
    for (int ks = 0; ks < 8; ks++)
        asm volatile(
            "{.reg .b64 da, db;\n"
            "mov.b64 da, {%24, %26};\n"
            "mov.b64 db, {%25, %26};\n"
            "wgmma.mma_async.sync.aligned.m64n48k16.f32.bf16.bf16 "
            "{%0,%1,%2,%3,%4,%5,%6,%7,%8,%9,%10,%11,%12,%13,%14,%15,%16,%17,%18,%19,%20,%21,%22,%23},"
            "da, db, 1, 1, 1, 1, 0;}"
            : ACC8(d, 0), ACC8(d, 8), ACC8(d, 16)
            : "r"(la + ks * 128), "r"(lb + (ks >> 2) * 640 + (ks & 3) * 2), "r"(0x40000040u));
    asm volatile("wgmma.commit_group.sync.aligned;" ::: "memory");
#pragma unroll
    for (int ks = 0; ks < 8; ks++)
        asm volatile(
            "{.reg .b64 da, db;\n"
            "mov.b64 da, {%16, %18};\n"
            "mov.b64 db, {%17, %18};\n"
            "wgmma.mma_async.sync.aligned.m64n32k16.f32.bf16.bf16 "
            "{%0,%1,%2,%3,%4,%5,%6,%7,%8,%9,%10,%11,%12,%13,%14,%15},"
            "da, db, 1, 1, 1, 1, 0;}"
            : ACC8(d, 24), ACC8(d, 32)
            : "r"(la + ks * 128), "r"(lb + 384 + (ks >> 2) * 640 + (ks & 3) * 2), "r"(0x40000040u));
    asm volatile("wgmma.commit_group.sync.aligned;" ::: "memory");
}
template <int N>
__device__ __forceinline__ void wgmma_wait(float (&d)[40]) {
    asm volatile("wgmma.wait_group.sync.aligned %40;" : ACC40(d) : "n"(N) : "memory");
}
template <bool HALF>
__device__ __forceinline__ void store_tile(uint32_t a, const float (&d)[40]) {
#pragma unroll
    for (int j = 0; j < 10; j += 2) {
        uint32_t r[4];
#pragma unroll
        for (int k = 0; k < 4; k++) {
            r[k] = pack2(d[4 * j + 2 * k], d[4 * j + 2 * k + 1]);
            if (HALF) r[k] = half2x(r[k]);
        }
        stsm4t(a + j * 1024, r[0], r[1], r[2], r[3]);
    }
}

template <int MODE>
__global__ void __launch_bounds__(THREADS, 1)
mpnn_kernel(const __nv_bfloat16* __restrict__ e_attr,
            const int* __restrict__ src, const int* __restrict__ dst,
            const __nv_bfloat16* __restrict__ w_msg,
            Scratch* __restrict__ sc,
            const __grid_constant__ CUtensorMap tm_wm, const __grid_constant__ CUtensorMap tm_wu,
            const __grid_constant__ CUtensorMap tm_x, const __grid_constant__ CUtensorMap tm_p,
            const __grid_constant__ CUtensorMap tm_out, const __grid_constant__ CUtensorMap tm_out2) {
    extern __shared__ __align__(1024) uint8_t smem[];
    const uint32_t sb = smem_u32(smem);
    Misc* ms = reinterpret_cast<Misc*>(smem + SM_MISC);
    const unsigned tid = threadIdx.x, lane = tid & 31;
    __builtin_assume(tid < THREADS);
    const unsigned cta = blockIdx.x;
    __builtin_assume(cta < NCTA);
    uint32_t dv[5], sv[5];
    if ((MODE & 1) && cta < NWR && tid >= 256) {
        const int* dp = dst + cta * EPC - 256;
        const int* sp = src + cta * EPC - 256;
        asm volatile("ld.global.nc.v4.u32 {%0,%1,%2,%3}, [%4];" : "=r"(dv[0]), "=r"(dv[1]), "=r"(dv[2]), "=r"(dv[3]) : "l"(dp - 768 + tid * 4));
        asm volatile("ld.global.nc.u32 %0, [%1];" : "=r"(dv[4]) : "l"(dp + 1024 + tid));
        asm volatile("ld.global.nc.v4.u32 {%0,%1,%2,%3}, [%4];" : "=r"(sv[0]), "=r"(sv[1]), "=r"(sv[2]), "=r"(sv[3]) : "l"(sp - 768 + tid * 4));
        asm volatile("ld.global.nc.u32 %0, [%1];" : "=r"(sv[4]) : "l"(sp + 1024 + tid));
    }
    const int warp = __shfl_sync(0xffffffffu, tid >> 5, 0);
    if (tid == 0) TSTAMP(0);

    const unsigned g = lane >> 2, q = lane & 3;
    const int node0 = cta * NPC;
    const uint32_t tile_a = sw<80>(((lane >> 4) & 1) * 8 + (lane & 7), (warp & 7) * 2 + ((lane >> 3) & 1));

    if (warp >= 8) {
        const unsigned tb = tid - 256;
        __builtin_assume(tb < 256);
        const bool writer = (MODE & 1) && cta < NWR;
        bar_arrive<3, 512>();
        unsigned htarget = 0;
        if (tb == 0 && MODE == 3) htarget = ld_relaxed32(&sc->sync[32]);
        if (tb < MISC_ZERO16) reinterpret_cast<uint4*>(ms)[tb] = make_uint4(0, 0, 0, 0);
        bar_sync<2, 256>();
        if (tb == 0) TSTAMP(17);
        if (writer) {
            uint32_t own[5], pos[5];
#pragma unroll
            for (int i = 0; i < 5; i++) {
                own[i] = (dv[i] * 55189u) >> 22;
                pos[i] = atoms_inc(sb + SM_MISC + own[i] * 4);
            }
            if (tb == 0) TSTAMP(18);
            uint32_t pmax = 0;
#pragma unroll
            for (int i = 0; i < 5; i++) {
                const uint32_t nl = dv[i] - own[i] * NPC;
                const uint32_t el1 = i < 4 ? tb * 4 + i + 1 : tb + 1025;
                sts32(sb + SM_LIST + own[i] * 128 + (pos[i] < MCAP ? pos[i] * 4 + 4 : 0), (sv[i] * 128u + nl) * 2048u + el1);
                pmax = max(pmax, pos[i]);
            }
            if (pmax >= MCAP) {
#pragma unroll
                for (int i = 0; i < 5; i++) {
                    if (pos[i] >= MCAP) {
                        const int k = atomicAdd(&ms->ovf, 1);
                        sc->ovf[cta * EPC + k] = make_uint2(dv[i], cta * EPC + (i < 4 ? tb * 4 + i : tb + 1024));
                    }
                }
                __threadfence();
            }
            if (tb == 0) TSTAMP(8);
            bar_sync<2, 256>();
            if (tb == 0) TSTAMP(19);
            {
                const uint32_t hdr = (uint32_t)ms->ovf << 11;
                uint4* gm = sc->mail + (tb >> 3) * RCHUNK + cta * 8 + (tb & 7);
                uint4 v[5];
                uint32_t c[5];
#pragma unroll
                for (int i = 0; i < 5; i++) {
                    v[i] = lds128(sb + SM_LIST + tb * 16 + i * 4096);
                    c[i] = lds32(sb + SM_MISC + (tb >> 3) * 4 + i * 128);
                }
#pragma unroll
                for (int i = 0; i < 5; i++) {
                    if ((tb & 7) == 0) v[i].x = hdr | c[i];
                    if (i < 4 || tb < SCHUNK - 1024) gm[i * 32 * RCHUNK] = v[i];
                }
            }
            if (tb == 0) TSTAMP(9);
            bar_sync<2, 256>();
            if (tb == 0) TSTAMP(23);
        }
        if (!(MODE & 2)) return;
        if (MODE == 3) {
            if (tb == 0) {
                asm volatile("red.release.gpu.global.add.u32 [%0], 1;" ::"l"(&sc->sync[32]) : "memory");
                htarget = htarget - htarget % NCTA + NCTA;
                int sp = 0;
                while ((int)(ld_poll32(&sc->sync[32]) - htarget) < 0 && ++sp < (1 << 22)) {}
                TSTAMP(24);
            }
            bar_sync<2, 256>();
        }
        uint32_t w[2][8];
        {
            const uint4* mine = sc->mail + cta * RCHUNK + (tb >> 2) * 8 + (tb & 3);
            const uint4* mine2 = tb + 256 < NWR * 4 ? mine + 512 : mine;
            asm volatile("ld.relaxed.gpu.global.v4.u32 {%0,%1,%2,%3}, [%16];\n"
                         "ld.relaxed.gpu.global.v4.u32 {%8,%9,%10,%11}, [%17];\n"
                         "ld.relaxed.gpu.global.v4.u32 {%4,%5,%6,%7}, [%16+64];\n"
                         "ld.relaxed.gpu.global.v4.u32 {%12,%13,%14,%15}, [%17+64];"
                         : "=r"(w[0][0]), "=r"(w[0][1]), "=r"(w[0][2]), "=r"(w[0][3]), "=r"(w[0][4]), "=r"(w[0][5]), "=r"(w[0][6]), "=r"(w[0][7]),
                           "=r"(w[1][0]), "=r"(w[1][1]), "=r"(w[1][2]), "=r"(w[1][3]), "=r"(w[1][4]), "=r"(w[1][5]), "=r"(w[1][6]), "=r"(w[1][7])
                         : "l"(mine), "l"(mine2) : "memory");
        }
        uint32_t hd[2];
        hd[0] = __shfl_sync(0xffffffffu, w[0][0], lane & ~3u);
        hd[1] = __shfl_sync(0xffffffffu, w[1][0], lane & ~3u);
        if (tb + 256 >= NWR * 4) hd[1] = 0;
        if (tb == 0) TSTAMP(10);
        int lim[2];
#pragma unroll
        for (int b = 0; b < 2; b++) {
            if ((hd[b] & 0x7ffu) > MCAP) { ms->wovf[(tb >> 2) + 64 * b] = hd[b] >> 11; ms->anyovf = 1; }
            lim[b] = (int)(hd[b] & 0x7ffu) - (int)(tb & 3) * 4;
        }
        const bool second = __any_sync(0xffffffffu, max(lim[0], lim[1]) >= 16);
        const uint32_t dummy = (96u + lane) << 11;
        if ((tb & 3) == 0) w[0][0] = w[1][0] = dummy;
        uint32_t rk[2][8];
        const uint32_t nc = smem_u32(ms->ncnt);
        auto hist = [&](int i0) {
#pragma unroll
            for (int b = 0; b < 2; b++)
#pragma unroll
                for (int i = i0; i < i0 + 4; i++) {
                    w[b][i] = lim[b] >= (i & 3) + (i >> 2) * 16 ? w[b][i] : dummy;
                    rk[b][i] = atoms_inc(nc + ((w[b][i] >> 9) & 0x1fc));
                }
        };
        hist(0);
        if (second) hist(4);
        const uint32_t wo = sb + SM_WOFF + (warp - 8) * 512;
        sts32(wo + 384 + lane * 4, 1u << 20);
        if (tb == 0) TSTAMP(20);
        bar_sync<2, 256>();
        int total;
        {
            const int c0 = lds32(nc + lane * 12), c1 = lds32(nc + lane * 12 + 4), c2 = lds32(nc + lane * 12 + 8);
            int s = c0 + c1 + c2;
#pragma unroll
            for (int d = 1; d < 32; d <<= 1) {
                const int t = __shfl_up_sync(0xffffffffu, s, d);
                if (lane >= d) s += t;
            }
            sts32(wo + lane * 12, s - c2 - c1 - c0);
            sts32(wo + lane * 12 + 4, s - c2 - c1);
            sts32(wo + lane * 12 + 8, s - c2);
            total = __shfl_sync(0xffffffffu, s, 31);
            if (warp == 15) {
                ms->off[lane * 3] = min(s - c2 - c1 - c0, CAP);
                ms->off[lane * 3 + 1] = min(s - c2 - c1, CAP);
                ms->off[lane * 3 + 2] = min(s - c2, CAP);
                if (lane == 31) { ms->off[96] = min(s, CAP); ms->total = s; if (s > CAP) ms->anyovf = 1; }
                if (total < CAP) {
                    const uint32_t pa = sb + SM_LIST + (total + lane) * 4;
                    sts32(pa, 79u << 23);
                    sts32(pa + LISTB, 0u);
                    if (lane < 16) sts32(pa + 128, 79u << 23);
                }
            }
            __syncwarp();
        }
        if (tb == 0) TSTAMP(22);
        const uint32_t eb = (tb >> 2) * EPC - 1;
        auto scatter = [&](int i0) {
#pragma unroll
            for (int b = 0; b < 2; b++)
#pragma unroll
                for (int i = i0; i < i0 + 4; i++) rk[b][i] += lds32(wo + ((w[b][i] >> 9) & 0x1fc));
#pragma unroll
            for (int b = 0; b < 2; b++)
#pragma unroll
                for (int i = i0; i < i0 + 4; i++) {
                    const uint32_t a = sb + SM_LIST + min(rk[b][i], (uint32_t)(CAP + 63)) * 4;
                    sts32(a, (w[b][i] >> 18) | ((w[b][i] << 12) & 0x3f800000u));
                    sts32(a + LISTB, eb + b * (64 * EPC) + (w[b][i] & 0x7ff));
                }
            if (total > CAP) {
#pragma unroll
                for (int b = 0; b < 2; b++)
#pragma unroll
                    for (int i = i0; i < i0 + 4; i++)
                        if (rk[b][i] >= CAP && rk[b][i] < (1u << 20))
                            sc->spill[cta * NSPILL + rk[b][i] - CAP] = make_uint2(node0 + ((w[b][i] >> 11) & 127), eb + b * (64 * EPC) + (w[b][i] & 0x7ff));
            }
        };
        scatter(0);
        if (second) scatter(4);
        if (tb == 0) TSTAMP(11);
    } else {
        unsigned target = 0;
        const uint32_t mb = smem_u32(ms->mbar);
        {
            const unsigned r0 = tid >> 4, c0 = tid & 15;
            bar_sync<3, 512>();
            cp_rows<8>(sb + SM_W12 + sw<256>(r0, c0), reinterpret_cast<const uint4*>(w_msg) + tid);
            cp16(sb + SM_W3S + w3sw(r0, c0), reinterpret_cast<const uint4*>(w_msg) + 4096 + tid);
            if (tid == 32 && MODE == 3) target = ld_relaxed32(&sc->sync[0]);
            if (tid == 160) asm volatile("prefetch.tensormap [%0];" ::"l"(&tm_p) : "memory");
            if (tid == 64) asm volatile("prefetch.tensormap [%0];" ::"l"(&tm_wu) : "memory");
            if (tid == 96) asm volatile("prefetch.tensormap [%0];" ::"l"(&tm_out) : "memory");
            if (tid == 128) asm volatile("prefetch.tensormap [%0];" ::"l"(&tm_out2) : "memory");
            if (tid == 0) {
                asm volatile("mbarrier.init.shared.b64 [%0], 1;" ::"r"(mb) : "memory");
                asm volatile("mbarrier.init.shared.b64 [%0], 1;" ::"r"(mb + 8) : "memory");
                asm volatile("mbarrier.init.shared.b64 [%0], 1;" ::"r"(mb + 16) : "memory");
                asm volatile("mbarrier.init.shared.b64 [%0], 1;" ::"r"(mb + 24) : "memory");
                asm volatile("fence.mbarrier_init.release.cluster;" ::: "memory");
                asm volatile("mbarrier.arrive.expect_tx.shared.b64 _, [%0], %1;" ::"r"(mb + 24), "n"(20480) : "memory");
                tma2d(sb + SM_X, &tm_x, 0, node0, mb + 24);
                tma2d(sb + SM_X + 10240, &tm_x, 64, node0, mb + 24);
                if (MODE & 2) {
                    tma_w(sb + SM_W12 + 16384, &tm_wm, 128, mb);
                    tma_w(sb + SM_WU, &tm_wu, 0, mb + 8);
                }
            }
            cp_commit();
        }
        const int wg = warp >> 2;
        float a0[40];
        cp_wait<0>();
        fence_async();
        target = target - target % NCTA + NCTA;
        if (tid == 32) sts32(sb + SM_TRASH, target);
        bar_sync<1, 256>();
        mbar_wait(mb + 24);
        if (tid == 0) TSTAMP(1);
        if (MODE & 1) {
            wgmma_issue(a0, sb + SM_W12 + wg * 32768, sb + SM_X);
            if (tid == 128) e_prefetch<0, 16>(e_attr, cta);
            wgmma_wait<0>(a0);
            if (tid == 0) TSTAMP(15);
            store_tile<true>(sb + SM_AGG + tile_a, a0);
            fence_async();
            bar_sync<1, 256>();
            if (tid == 0) TSTAMP(16);
            if (tid == 0) {
                tma_store(&tm_p, sb + SM_AGG, 0, node0);
                tma_store(&tm_p, sb + SM_AGG + 10240, 64, node0);
                asm volatile("cp.async.bulk.commit_group;" ::: "memory");
                e_prefetch<16, 8>(e_attr, cta);
            }
        }
        if (!(MODE & 2)) {
            asm volatile("cp.async.bulk.wait_group 0;" ::: "memory");
            return;
        }
        float a1[40];
        mbar_wait(mb);
        wgmma_issue(a0, sb + SM_W12 + wg * 32768 + 16384, sb + SM_X);
        mbar_wait(mb + 8);
        wgmma_issue(a1, sb + SM_WU + wg * 32768, sb + SM_X);
        wgmma_wait<0>(a0);
        asm volatile("" : ACC40(a1)::"memory");
        bar_sync<1, 256>();
        if (tid == 0) {
            if (MODE == 3) {
                TSTAMP(4);
                asm volatile("cp.async.bulk.wait_group 0;" ::: "memory");
                TSTAMP(2);
                asm volatile("red.release.gpu.global.add.u32 [%0], 1;" ::"l"(&sc->sync[0]) : "memory");
                TSTAMP(3);
                e_prefetch<24, 16>(e_attr, cta);
            }
        }
        store_tile<false>(sb + SM_Q + tile_a, a0);
        {
            uint32_t f[4];
            const unsigned r = lane & 7, mat = lane >> 3;
            ldsm4t(f, sb + SM_W3S + w3sw(4 * (r >> 1) + (r & 1) + 2 * (mat >> 1), warp * 2 + (mat & 1)));
            reinterpret_cast<uint4*>(smem + SM_W3F)[tid] = make_uint4(half2x(f[0]), half2x(f[1]), half2x(f[2]), half2x(f[3]));
        }
#pragma unroll
        for (int j = 0; j < 10; j++)
            *reinterpret_cast<float4*>(smem + r_off(j) + tid * 16) =
                make_float4(0.5f * a1[4 * j], 0.5f * a1[4 * j + 1], 0.5f * a1[4 * j + 2], 0.5f * a1[4 * j + 3]);
        if (tid >= 224) *reinterpret_cast<uint4*>(smem + SM_ZL + (lane >> 3) * 1024 + (lane & 7) * 16) = make_uint4(0, 0, 0, 0);
        if (tid == 0) TSTAMP(25);
        if (tid == 32 && MODE == 3) {
            TSTAMP(7);
            int sp = 0;
            while ((int)(ld_poll32(&sc->sync[0]) - target) < 0 && ++sp < (1 << 22)) {}
            TSTAMP(5);
        }
    }
    bar_sync<0, 512>();
    if (tid == 0) TSTAMP(6);

    const int M = ms->off[96];
    const int T = (M + 15) >> 4;
    const int rg = (warp & 3) * 4 + (warp >> 2);
    const int s = range_start(rg, T) * 16;
    const int e = min(range_start(rg + 1, T) * 16, M);
    const uint32_t ring = sb + SM_RING + rg * SLOT;
    {
        const unsigned fr = lane >> 3, fc = lane & 7;
        const char* Pb0 = reinterpret_cast<const char*>(sc->P) + ((fc ^ fr) << 4);
        const char* Pb1 = reinterpret_cast<const char*>(sc->P) + ((fc ^ fr ^ 4) << 4);
        const char* Eb = reinterpret_cast<const char*>(e_attr) + (lane & 1) * 16;
        asm volatile("" : "+l"(Pb0), "+l"(Pb1), "+l"(Eb));
        const uint32_t fdst = ring + lane * 16;
        const unsigned ledge = (lane & 6) | ((lane ^ (lane >> 3) ^ 1) & 1);
        const uint32_t lz = ((lane & 1) ? ring + ledge * 128 : sb + SM_ZL) + (((lane >> 4) ^ ledge) << 4);
        const uint32_t w3a = sb + SM_W3F + lane * 16;
        uint32_t sn[4], ei;
        auto fidx = [&](int tb) {
#pragma unroll
            for (int i = 0; i < 4; i++) sn[i] = lds16(sb + SM_LIST + (tb + fr) * 4 + i * 16);
            ei = lds32(sb + SM_EID + (tb + (lane >> 1)) * 4);
        };
        auto fetchP = [&](int h, int skip) {
#pragma unroll
            for (int i = 0; i < 4; i++) {
                if (h == 0) cp16g<256, 0>(fdst + i * 512, (i & 1) ? Pb1 : Pb0, sn[i], skip);
                else cp16g<256, 128>(fdst + 2048 + i * 512, (i & 1) ? Pb1 : Pb0, sn[i], skip);
            }
        };
        auto fetchE = [&](int skip) { cp16g<32, 0>(fdst + 4096, Eb, ei, skip); };
        int lo = s;
        auto first_fetch = [&]() {
            const int skip = lo >= e;
            fetchE(skip);
            fetchP(0, skip);
            cp_commit();
            fetchP(1, skip);
            cp_commit();
        };
        fidx(lo);
        if (warp >= 4) asm volatile("bar.sync %0, 256;" ::"r"(4 + (warp >> 2)) : "memory");
        fetchE(lo >= e);
        fetchP(0, lo >= e);
        cp_commit();
        if (warp < 12) asm volatile("bar.arrive %0, 256;" ::"r"(5 + (warp >> 2)) : "memory");
        fetchP(1, lo >= e);
        cp_commit();
        if (tid == 480) tma_w(sb + SM_WU + 16384, &tm_wu, 128, smem_u32(ms->mbar) + 16);
        {
            const int nd = warp * 5 + min(lane, 4u);
            unsigned em = __ballot_sync(0xffffffffu, ms->off[nd] == ms->off[nd + 1]) & 31u;
            while (em) {
                const int k = __ffs(em) - 1;
                em &= em - 1;
                *reinterpret_cast<uint2*>(smem + SM_AGG + sw<80>(warp * 5 + k, lane >> 1) + (lane & 1) * 8) = make_uint2(0, 0);
            }
        }
        if (lane == 0) {
            uint32_t desc = 0;
            if (s < e) {
                const int nl = lds32(sb + SM_LIST + (e - 1) * 4) >> 23;
                const int o1 = ms->off[nl + 1];
                if (ms->off[nl] >= s && o1 > e) {
                    desc = nl;
                    int s2 = e;
                    for (int r2 = rg + 1; s2 < o1; r2++) {
                        const int e2 = range_start(r2 + 1, T) * 16;
                        if (s2 < e2) desc |= 256u << r2;
                        s2 = e2;
                    }
                }
            }
            ms->cnt[rg] = desc;
        }
        while (lo < e) {
            int tb = lo & ~15;
            const int nb = lds32(sb + SM_LIST + lo * 4) >> 23;
            const int hi = min(e, ms->off[min(nb + 8, 96)]);
            const int o0 = ms->off[nb + 2 * q];
            const uint32_t cn0 = ms->off[nb + 2 * q + 1] - o0;
            const uint32_t cn1 = ms->off[nb + 2 * q + 2] - o0 - cn0;
            uint32_t fa, fs;
            {
                const int nd = nb + (lane & 7);
                const int p0 = ms->off[nd], p1 = ms->off[nd + 1];
                const bool full = p0 >= s && p1 <= e && p1 > p0;
                const bool fst = p0 < s && p1 > s;
                const bool lst = p0 >= s && p0 < e && p1 > e;
                fa = full ? sb + SM_AGG + sw<80>(nd, lane >> 3)
                          : (fst ? ring + 4608 : lst ? ring + 4864 : sb + SM_TRASH) + (lane >> 3) * 16;
                fs = full ? 10240 : 128;
            }
            float acc[8][4];
#pragma unroll
            for (int m = 0; m < 8; m++)
#pragma unroll
                for (int k = 0; k < 4; k++) acc[m][k] = 0.f;
            uint32_t qf[4][4];
            const uint32_t qa = sb + SM_Q + sw<80>(min(nb + (int)(lane & 7), 79), lane >> 3);
#pragma unroll
            for (int j = 0; j < 4; j++) ldsm4t(qf[j], (qa ^ ((j & 1) << 6)) + (j >> 1) * 10240);
            uint32_t q0, q1, ss0, ss1;
            uint2 e0, e1;
            int last;
            float c[2][2][2][4];
            auto top = [&]() {
                const uint32_t u = tb + g - o0;
                q0 = (u < cn0 ? 0x3F00u : 0u) | (u - cn0 < cn1 ? 0x3F000000u : 0u);
                q1 = (u + 8 < cn0 ? 0x3F00u : 0u) | (u + 8 - cn0 < cn1 ? 0x3F000000u : 0u);
                tb += 16;
                fidx(tb);
                cp_wait<1>();
                __syncwarp();
                e0 = lds64(ring + 4096 + lane * 8);
                e1 = lds64(ring + 4096 + 256 + lane * 8);
            };
            auto stageA = [&](int j, float (&cc)[2][2][4]) {
                if (j == 2) { cp_wait<1>(); __syncwarp(); }
#pragma unroll
                for (int mm = 0; mm < 2; mm++) {
                    const int m = 2 * j + mm;
                    const uint4 wf = lds128(w3a + m * 512);
                    ldsm4tf(cc[mm][0], (lz ^ ((m & 3) << 5)) + (m >> 2) * 2048);
                    ldsm4tf(cc[mm][1], (lz ^ ((m & 3) << 5)) + (m >> 2) * 2048 + 1024);
                    mma8(cc[mm][0], qf[j][2 * mm], qf[j][2 * mm + 1], q0);
                    mma8(cc[mm][1], qf[j][2 * mm], qf[j][2 * mm + 1], q1);
                    mma16(cc[mm][0], wf.x, wf.y, wf.z, wf.w, e0.x, e0.y);
                    mma16(cc[mm][1], wf.x, wf.y, wf.z, wf.w, e1.x, e1.y);
                }
                if (j & 1) {
                    __syncwarp();
                    if (j == 1) fetchE(last);
                    fetchP(j >> 1, last);
                    cp_commit();
                }
            };
            auto stageB = [&](int j, float (&cc)[2][2][4]) {
#pragma unroll
                for (int mm = 0; mm < 2; mm++) {
                    const uint32_t a0 = pack2(silu_h(cc[mm][0][0]), silu_h(cc[mm][0][1]));
                    const uint32_t a1 = pack2(silu_h(cc[mm][0][2]), silu_h(cc[mm][0][3]));
                    const uint32_t a2 = pack2(silu_h(cc[mm][1][0]), silu_h(cc[mm][1][1]));
                    const uint32_t a3 = pack2(silu_h(cc[mm][1][2]), silu_h(cc[mm][1][3]));
                    mma16(acc[2 * j + mm], a0, a1, a2, a3, ss0, ss1);
                }
            };
            top();
            stageA(0, c[0]);
#pragma unroll 1
            for (;;) {
                ss0 = movm(q0);
                ss1 = movm(q1);
                last = tb >= hi;
                stageA(1, c[1]); stageB(0, c[0]);
                stageA(2, c[0]); stageB(1, c[1]);
                stageA(3, c[1]); stageB(2, c[0]);
                top();
                stageA(0, c[0]);
                stageB(3, c[1]);
                if (last) break;
            }
#pragma unroll
            for (int j = 0; j < 4; j++)
                stsm4t((fa ^ ((j & 1) << 6)) + (j >> 1) * fs, pack2(acc[2 * j][0], acc[2 * j][1]), pack2(acc[2 * j][2], acc[2 * j][3]),
                       pack2(acc[2 * j + 1][0], acc[2 * j + 1][1]), pack2(acc[2 * j + 1][2], acc[2 * j + 1][3]));
            lo = hi;
            if (lo < e) {
                cp_wait<0>();
                __syncwarp();
                fidx(lo & ~15);
                first_fetch();
            }
        }
    }
    if (warp >= 8) {
        const int tb = tid - 256;
        const int r1 = (warp - 8) * 2 + (lane >> 4);
        const unsigned hl = lane & 15;
        const bool slow = ms->anyovf;
        bar_sync<0, 512>();
        if (tb == 0) TSTAMP(21);
        const uint32_t desc = lds32(sb + SM_MISC + r1 * 4);
        uint4 u = lds128(sb + SM_RING + r1 * SLOT + 4864 + hl * 16);
        uint4 u2 = lds128(sb + SM_RING + min(r1 + 1, 15) * SLOT + 4608 + hl * 16);
        if (desc) {
            const int nl = desc & 255;
            float v[8];
            v[0] = __uint_as_float(u.x << 16); v[1] = __uint_as_float(u.x & 0xffff0000u);
            v[2] = __uint_as_float(u.y << 16); v[3] = __uint_as_float(u.y & 0xffff0000u);
            v[4] = __uint_as_float(u.z << 16); v[5] = __uint_as_float(u.z & 0xffff0000u);
            v[6] = __uint_as_float(u.w << 16); v[7] = __uint_as_float(u.w & 0xffff0000u);
            for (uint32_t mk = desc >> 8; mk; mk &= mk - 1) {
                const int r2 = __ffs(mk) - 1;
                if (r2 != r1 + 1) u2 = lds128(sb + SM_RING + r2 * SLOT + 4608 + hl * 16);
                v[0] += __uint_as_float(u2.x << 16); v[1] += __uint_as_float(u2.x & 0xffff0000u);
                v[2] += __uint_as_float(u2.y << 16); v[3] += __uint_as_float(u2.y & 0xffff0000u);
                v[4] += __uint_as_float(u2.z << 16); v[5] += __uint_as_float(u2.z & 0xffff0000u);
                v[6] += __uint_as_float(u2.w << 16); v[7] += __uint_as_float(u2.w & 0xffff0000u);
            }
            *reinterpret_cast<uint4*>(smem + SM_AGG + sw<80>(nl, hl)) =
                make_uint4(pack2(v[0], v[1]), pack2(v[2], v[3]), pack2(v[4], v[5]), pack2(v[6], v[7]));
        }
        if (slow) {
            __threadfence();
            bar_sync<2, 256>();
            float* ext = reinterpret_cast<float*>(smem + SM_EXT);
            for (int i = tb; i < 80 * 128; i += 256) ext[i] = 0.f;
            bar_sync<2, 256>();
            const char* Pb = reinterpret_cast<const char*>(sc->P);
            for (int w = -1; w < NWR; w++) {
                const int cnt = w < 0 ? ms->total - CAP : ms->wovf[w];
                for (int k = warp - 8; k < cnt; k += 8) {
                    uint2 en;
                    const uint2* ep = w < 0 ? sc->spill + cta * NSPILL + k : sc->ovf + w * EPC + k;
                    asm volatile("ld.relaxed.gpu.global.v2.u32 {%0,%1}, [%2];" : "=r"(en.x), "=r"(en.y) : "l"(ep) : "memory");
                    const int nl = (int)en.x - node0;
                    const uint32_t eid = en.y;
                    if (nl < 0 || nl >= NPC) continue;
                    const uint32_t sn = src[eid];
                    for (int u = 0; u < 4; u++) {
                        const int f = lane * 4 + u;
                        float h = 0.f;
                        for (int kk = 0; kk < 16; kk++)
                            h = fmaf(__bfloat162float(e_attr[(size_t)eid * 16 + kk]), __bfloat162float(w_msg[(256 + kk) * 128 + f]), h);
                        h += __bfloat162float(*reinterpret_cast<const __nv_bfloat16*>(smem + SM_Q + sw<80>(nl, f >> 3) + (f & 7) * 2));
                        h = 0.5f * h + __bfloat162float(*reinterpret_cast<const __nv_bfloat16*>(Pb + sn * 256 + f * 2));
                        atomicAdd(&ext[nl * 128 + f], __bfloat162float(__float2bfloat16_rn(silu_h(h))));
                    }
                }
            }
            bar_sync<2, 256>();
            for (int i = tb; i < 80 * 128; i += 256) {
                const int r = i >> 7, f = i & 127;
                __nv_bfloat16* pp = reinterpret_cast<__nv_bfloat16*>(smem + SM_AGG + sw<80>(r, f >> 3) + (f & 7) * 2);
                *pp = __float2bfloat16_rn(__bfloat162float(*pp) + 0.5f * ext[i]);
            }
        }
        fence_async();
        bar_arrive<4, 512>();
        return;
    }
    {
        const int wg = warp >> 2;
        float a0[40];
        bar_arrive<0, 512>();
        fence_async();
#pragma unroll
        for (int j = 0; j < 10; j++) {
            const float4 v = *reinterpret_cast<const float4*>(smem + r_off(j) + tid * 16);
            a0[4 * j] = v.x; a0[4 * j + 1] = v.y; a0[4 * j + 2] = v.z; a0[4 * j + 3] = v.w;
        }
        mbar_wait(smem_u32(ms->mbar) + 16);
        bar_sync<4, 512>();
        if (tid == 0) TSTAMP(14);
        asm volatile("" : ACC40(a0)::"memory");
        wgmma_issue_split(a0, sb + SM_WU + wg * 32768 + 16384, sb + SM_AGG);
        auto emit = [&](int j0, int j1, const CUtensorMap* tm) {
#pragma unroll
            for (int j = j0; j < j1; j += 2) {
                uint32_t r[4];
#pragma unroll
                for (int k = 0; k < 4; k++) r[k] = pack2(silu_h(a0[4 * j + 2 * k]), silu_h(a0[4 * j + 2 * k + 1]));
                stsm4t(sb + SM_OUT + tile_a + j * 1024, r[0], r[1], r[2], r[3]);
            }
            fence_async();
            if (wg == 0) bar_sync<1, 128>(); else bar_sync<3, 128>();
            if ((tid & 127) == 0) {
                tma_store(tm, sb + SM_OUT + wg * 10240 + j0 * 1024, wg * 64, node0 + j0 * 8);
                asm volatile("cp.async.bulk.commit_group;" ::: "memory");
            }
        };
        asm volatile("wgmma.wait_group.sync.aligned 1;" : ACC8(a0, 0), ACC8(a0, 8), ACC8(a0, 16)::"memory");
        if (tid == 0) TSTAMP(26);
        emit(0, 6, &tm_out);
        asm volatile("wgmma.wait_group.sync.aligned 0;" : ACC8(a0, 24), ACC8(a0, 32)::"memory");
        emit(6, 10, &tm_out2);
        if ((tid & 127) == 0) asm volatile("cp.async.bulk.wait_group.read 0;" ::: "memory");
    }
    if (tid == 0) TSTAMP(12);
}

}

typedef CUresult (*EncodeFn)(CUtensorMap*, CUtensorMapDataType, cuuint32_t, void*, const cuuint64_t*, const cuuint64_t*,
                             const cuuint32_t*, const cuuint32_t*, CUtensorMapInterleave, CUtensorMapSwizzle,
                             CUtensorMapL2promotion, CUtensorMapFloatOOBfill);

static void make_map(EncodeFn enc, CUtensorMap* tm, const void* base, int rows, int box_rows) {
    const cuuint64_t dims[2] = {128, (cuuint64_t)rows};
    const cuuint64_t strides[1] = {256};
    const cuuint32_t box[2] = {64, (cuuint32_t)box_rows};
    const cuuint32_t estr[2] = {1, 1};
    enc(tm, CU_TENSOR_MAP_DATA_TYPE_BFLOAT16, 2, const_cast<void*>(base), dims, strides, box, estr, CU_TENSOR_MAP_INTERLEAVE_NONE,
        CU_TENSOR_MAP_SWIZZLE_128B, CU_TENSOR_MAP_L2_PROMOTION_L2_256B, CU_TENSOR_MAP_FLOAT_OOB_FILL_NONE);
}

extern "C" void kernel_launch(void* const* d_in, const int* in_sizes, int n_in, void* d_out, int out_size) {
    const __nv_bfloat16* e_attr = (const __nv_bfloat16*)d_in[1];
    const int* src = (const int*)d_in[2];
    const int* dst = (const int*)d_in[3];
    const __nv_bfloat16* w_msg = (const __nv_bfloat16*)d_in[4];

    static int fused = -1;
    static Scratch* sc = nullptr;
    static EncodeFn enc = nullptr;
    if (fused < 0) {
        cudaFuncSetAttribute(mpnn_kernel<1>, cudaFuncAttributeMaxDynamicSharedMemorySize, SM_ALLOC);
        cudaFuncSetAttribute(mpnn_kernel<2>, cudaFuncAttributeMaxDynamicSharedMemorySize, SM_ALLOC);
        cudaFuncSetAttribute(mpnn_kernel<3>, cudaFuncAttributeMaxDynamicSharedMemorySize, SM_ALLOC);
        int dev = 0, sms = 0, occ = 0;
        cudaGetDevice(&dev);
        cudaDeviceGetAttribute(&sms, cudaDevAttrMultiProcessorCount, dev);
        cudaOccupancyMaxActiveBlocksPerMultiprocessor(&occ, mpnn_kernel<3>, THREADS, SM_ALLOC);
        cudaGetSymbolAddress((void**)&sc, g_sc);
        cudaDriverEntryPointQueryResult qr;
        cudaGetDriverEntryPoint("cuTensorMapEncodeTiled", (void**)&enc, cudaEnableDefault, &qr);
        fused = (sms * occ >= NCTA) ? 1 : 0;
    }
    CUtensorMap tm_wm, tm_wu, tm_x, tm_p, tm_out, tm_out2;
    make_map(enc, &tm_out, d_out, NN, 48);
    make_map(enc, &tm_out2, d_out, NN, NPC - 48);
    make_map(enc, &tm_p, sc->P, NN, NPC);
    make_map(enc, &tm_x, d_in[0], NN, 80);
    make_map(enc, &tm_wm, d_in[4], 272, 128);
    make_map(enc, &tm_wu, d_in[5], 256, 128);
    if (fused) {
        mpnn_kernel<3><<<NCTA, THREADS, SM_ALLOC, cudaStreamPerThread>>>(e_attr, src, dst, w_msg, sc, tm_wm, tm_wu, tm_x, tm_p, tm_out, tm_out2);
    } else {
        mpnn_kernel<1><<<NCTA, THREADS, SM_ALLOC, cudaStreamPerThread>>>(e_attr, src, dst, w_msg, sc, tm_wm, tm_wu, tm_x, tm_p, tm_out, tm_out2);
        mpnn_kernel<2><<<NCTA, THREADS, SM_ALLOC, cudaStreamPerThread>>>(e_attr, src, dst, w_msg, sc, tm_wm, tm_wu, tm_x, tm_p, tm_out, tm_out2);
    }
}
```
